```python
import torch

def _softmax(x, axis=-1):
    return torch.softmax(x, dim=axis)
def _gelu(x):
    return torch.nn.functional.gelu(x, approximate="tanh")
def _silu(x):
    return torch.nn.functional.silu(x)
def _sigmoid(x):
    return torch.sigmoid(x)
def _layernorm(x, axis=-1, eps=1e-5):
    m = x.mean(dim=axis, keepdim=True)
    v = x.var(dim=axis, keepdim=True, unbiased=False)
    return (x - m) / torch.sqrt(v + eps)
def _scatter_add(tgt, idx, src, axis=0):
    return tgt.clone().index_add_(axis, idx, src)
def _segment_sum(src, seg, n):
    out = torch.zeros((n,) + src.shape[1:], dtype=src.dtype)
    return out.index_add_(0, seg, src)
def _pad(x, pw):
    flat = tuple(v for pair in reversed(pw) for v in pair)
    return torch.nn.functional.pad(x, flat)

kernel_name = 'standalone__gqa_block_cached__decode'

def setup_inputs():

    _w = (lambda a: (lambda t: t.to(torch.bfloat16) if t.is_floating_point() else t)(torch.as_tensor(a)))
    B, Sq, D = 2, 1, 576
    Hq, Hkv, Sk, Dh = 32, 16, 32768, 128
    assert Hq % Hkv == 0, (Hq, Hkv)
    return {
        "x": _w((lambda *s: torch.randn(*s, dtype=torch.bfloat16) * 0.8)(B, Sq, D)),
        "k_cache": _w((lambda *s: torch.randn(*s, dtype=torch.bfloat16) * 0.8)(B, Hkv, Sk, Dh)),
        "v_cache": _w((lambda *s: torch.randn(*s, dtype=torch.bfloat16) * 0.05)(B, Hkv, Sk, Dh)),
        "wq": _w((lambda *s: torch.randn(*s, dtype=torch.bfloat16) * 0.8)(D, Hq * Dh) * (D ** -0.5)),
        "wo": _w((lambda *s: torch.randn(*s, dtype=torch.bfloat16) * 0.05)(Hq * Dh, D) * ((Hq * Dh) ** -0.5)),
    }

def reference(x, k_cache, v_cache, wq, wo):
    B, Sq, D = x.shape
    Hq, Dh = 32, 128
    Hkv = k_cache.shape[1]
    rep = Hq // Hkv
    q = (lambda x, *d: x.permute(*d))((x @ wq).reshape(B, Sq, Hq, Dh), 0, 2, 1, 3)
    k = (lambda x, n, axis: torch.repeat_interleave(x, n, dim=axis))(k_cache, rep, axis=1)
    v = (lambda x, n, axis: torch.repeat_interleave(x, n, dim=axis))(v_cache, rep, axis=1)
    scores = torch.einsum("bhqd,bhkd->bhqk", q, k) * (Dh ** -0.5)
    p = _softmax(scores, axis=-1)
    o = torch.einsum("bhqk,bhkd->bhqd", p, v)
    return (lambda x, *d: x.permute(*d))(o, 0, 2, 1, 3).reshape(B, Sq, Hq * Dh) @ wo
```

```cpp
#include <cuda_runtime.h>
#include <cuda_bf16.h>
#include <cuda.h>
#include <stdint.h>

namespace {

constexpr int kB = 2, kD = 576, kHQ = 32, kHKV = 16, kSK = 32768, kDH = 128;
constexpr int kNG = kB * kHKV;
#define CFG_TILE 64
#define CFG_STAGES 4
constexpr int TILE = CFG_TILE;
constexpr int STAGES = CFG_STAGES;
#define CFG_EARLY 2
constexpr int EARLY_STAGES = CFG_EARLY < STAGES ? CFG_EARLY : STAGES - 1;
constexpr int TPG = kSK / TILE;
constexpr int NTILES = kNG * TPG;
constexpr int NCTA = 132;
constexpr int NJOB = 128;
constexpr int TILE_BYTES = TILE * kDH * 2;
constexpr int HALF_BYTES = TILE_BYTES / 2;
constexpr int STAGE_BYTES = 2 * TILE_BYTES;
constexpr int KPW = TILE / 4;
constexpr int NT_QK = KPW / 8;
constexpr int NKB = TILE / 16;
constexpr int NTHREADS = 288;
constexpr int WO_BYTES = 32 * kD * 2;

static_assert(TILE == 32 || TILE == 64 || TILE == 128, "tile");

constexpr int SM_RING = 0;
constexpr int SM_WO = SM_RING + STAGES * STAGE_BYTES;
constexpr int SM_Q = SM_WO + WO_BYTES;
constexpr int SM_SX = SM_Q + 16384;
constexpr int SM_RED = SM_SX + 2 * (TILE / 8) * 8 * 8;
constexpr int SM_OF = SM_RED + 8 * 64 * 4;
constexpr int SM_BAR = SM_OF + 128;
constexpr int SM_TIDX = SM_BAR + 8 * (2 * STAGES + 1);
constexpr int SM_FRONT = SM_TIDX + 4 * STAGES;
constexpr int SM_QFLAG = SM_FRONT + 16;
constexpr int SM_TOTAL = SM_QFLAG + 4 * kNG;
constexpr int SMEM_BYTES = SM_TOTAL + 1024;

__device__ unsigned int g_ctr;
__device__ __align__(16) uint32_t g_q[kB * kHQ * kDH / 2];
__device__ __align__(16) float g_po[kNG][8][NCTA][32];
__device__ __align__(16) float2 g_pml[kNG][8][NCTA];
__device__ __align__(16) float g_op[kB][kHKV][8][kD];
__device__ unsigned int g_done[kNG * 32];
__device__ unsigned int g_done2[kNG * 32];

#define STAMP(i) do { } while (0)
__device__ float f_q[kB * kHQ * kDH];
__device__ float f_po[kB * kHQ][64][kDH];
__device__ float2 f_pml[kB * kHQ][64];
__device__ float f_o[kB * kHQ * kDH];

__device__ __forceinline__ uint32_t smem_u32(const void* p) { return (uint32_t)__cvta_generic_to_shared(p); }
__device__ __forceinline__ void mbar_init(uint32_t bar, uint32_t cnt) {
    asm volatile("mbarrier.init.shared::cta.b64 [%0], %1;" ::"r"(bar), "r"(cnt) : "memory");
}
__device__ __forceinline__ void mbar_expect_tx(uint32_t bar, uint32_t bytes) {
    asm volatile("mbarrier.arrive.expect_tx.shared::cta.b64 _, [%0], %1;" ::"r"(bar), "r"(bytes) : "memory");
}
__device__ __forceinline__ void mbar_arrive(uint32_t bar) {
    asm volatile("mbarrier.arrive.shared::cta.b64 _, [%0];" ::"r"(bar) : "memory");
}
__device__ __forceinline__ bool mbar_try(uint32_t bar, uint32_t parity) {
    uint32_t ok;
    asm volatile(
        "{\n.reg .pred p;\nmbarrier.try_wait.parity.shared::cta.b64 p, [%1], %2;\nselp.u32 %0, 1, 0, p;\n}"
        : "=r"(ok) : "r"(bar), "r"(parity) : "memory");
    return ok != 0;
}
constexpr uint32_t SPIN_LIMIT = 1u << 24;
__device__ __forceinline__ void mbar_wait(uint32_t bar, uint32_t parity) {
    uint32_t n = 0;
    while (!mbar_try(bar, parity)) {
        if (++n > SPIN_LIMIT) __trap();
    }
}
__device__ __forceinline__ void tma2d(uint32_t dst, const CUtensorMap* tm, int c0, int c1, uint32_t bar, uint64_t pol) {
    asm volatile(
        "cp.async.bulk.tensor.2d.shared::cluster.global.mbarrier::complete_tx::bytes.L2::cache_hint "
        "[%0], [%1, {%3, %4}], [%2], %5;" ::"r"(dst), "l"(tm), "r"(bar), "r"(c0), "r"(c1), "l"(pol) : "memory");
}
__device__ __forceinline__ void bulk_load(uint32_t dst, const void* src, uint32_t bytes, uint32_t bar) {
    asm volatile("cp.async.bulk.shared::cluster.global.mbarrier::complete_tx::bytes [%0], [%1], %2, [%3];"
                 ::"r"(dst), "l"(src), "r"(bytes), "r"(bar) : "memory");
}
__device__ __forceinline__ void named_bar(int id, int n) { asm volatile("bar.sync %0, %1;" ::"r"(id), "r"(n) : "memory"); }
__device__ __forceinline__ void ldsm4(uint32_t a, uint32_t& r0, uint32_t& r1, uint32_t& r2, uint32_t& r3) {
    asm volatile("ldmatrix.sync.aligned.m8n8.x4.shared.b16 {%0,%1,%2,%3}, [%4];"
                 : "=r"(r0), "=r"(r1), "=r"(r2), "=r"(r3) : "r"(a) : "memory");
}
__device__ __forceinline__ void ldsm4t(uint32_t a, uint32_t& r0, uint32_t& r1, uint32_t& r2, uint32_t& r3) {
    asm volatile("ldmatrix.sync.aligned.m8n8.x4.trans.shared.b16 {%0,%1,%2,%3}, [%4];"
                 : "=r"(r0), "=r"(r1), "=r"(r2), "=r"(r3) : "r"(a) : "memory");
}
__device__ __forceinline__ void mma_bf16(float (&c)[4], uint32_t a0, uint32_t a2, uint32_t b0, uint32_t b1) {
    asm volatile(
        "mma.sync.aligned.m16n8k16.row.col.f32.bf16.bf16.f32 {%0,%1,%2,%3}, {%4,%5,%6,%7}, {%8,%9}, {%0,%1,%2,%3};"
        : "+f"(c[0]), "+f"(c[1]), "+f"(c[2]), "+f"(c[3])
        : "r"(a0), "r"(0u), "r"(a2), "r"(0u), "r"(b0), "r"(b1));
}
__device__ __forceinline__ uint4 ld_relaxed_v4(const void* p) {
    uint4 v;
    asm volatile("ld.relaxed.gpu.global.v4.u32 {%0,%1,%2,%3}, [%4];" : "=r"(v.x), "=r"(v.y), "=r"(v.z), "=r"(v.w) : "l"(p) : "memory");
    return v;
}
__device__ __forceinline__ uint2 ld_relaxed_v2(const void* p) {
    uint2 v;
    asm volatile("ld.relaxed.gpu.global.v2.u32 {%0,%1}, [%2];" : "=r"(v.x), "=r"(v.y) : "l"(p) : "memory");
    return v;
}
__device__ __forceinline__ void st_relaxed_v4(void* p, uint4 v) {
    asm volatile("st.relaxed.gpu.global.v4.u32 [%0], {%1,%2,%3,%4};" ::"l"(p), "r"(v.x), "r"(v.y), "r"(v.z), "r"(v.w) : "memory");
}
__device__ __forceinline__ void st_relaxed_v2(void* p, uint2 v) {
    asm volatile("st.relaxed.gpu.global.v2.u32 [%0], {%1,%2};" ::"l"(p), "r"(v.x), "r"(v.y) : "memory");
}
__device__ __forceinline__ void st_relaxed_u32(void* p, uint32_t v) {
    asm volatile("st.relaxed.gpu.global.u32 [%0], %1;" ::"l"(p), "r"(v) : "memory");
}
__device__ __forceinline__ uint4 ld_nc_v4(const void* p) {
    uint4 v;
    asm volatile("ld.global.nc.L1::no_allocate.v4.u32 {%0,%1,%2,%3}, [%4];" : "=r"(v.x), "=r"(v.y), "=r"(v.z), "=r"(v.w) : "l"(p));
    return v;
}
__device__ __forceinline__ uint32_t ld_nc_u16(const void* p) {
    unsigned short v;
    asm volatile("ld.global.nc.u16 %0, [%1];" : "=h"(v) : "l"(p));
    return (uint32_t)v;
}
__device__ __forceinline__ uint32_t enc(float f) {
    uint32_t u = __float_as_uint(f);
    return u == 0u ? 0x80000000u : u;
}
__device__ __forceinline__ bool valid4(const uint4& v) { return v.x != 0u && v.y != 0u && v.z != 0u && v.w != 0u; }
__device__ __forceinline__ float bf_lo(uint32_t w) { return __uint_as_float(w << 16); }
__device__ __forceinline__ float bf_hi(uint32_t w) { return __uint_as_float(w & 0xffff0000u); }
__device__ __forceinline__ uint32_t pack_bf16(float lo, float hi) {
    uint32_t r;
    asm("cvt.rn.bf16x2.f32 %0, %1, %2;" : "=r"(r) : "f"(hi), "f"(lo));
    return r;
}
__device__ __forceinline__ float ex2(float x) {
    float y;
    asm("ex2.approx.ftz.f32 %0, %1;" : "=f"(y) : "f"(x));
    return y;
}

constexpr float kScaleLog2 = 0.08838834764831845f * 1.4426950408889634f;

__device__ __forceinline__ void red_add(unsigned int* p, unsigned int v) {
    asm volatile("red.relaxed.gpu.global.add.u32 [%0], %1;" ::"l"(p), "r"(v) : "memory");
}
__device__ __forceinline__ uint32_t ld_relaxed_u32(const void* p) {
    uint32_t v;
    asm volatile("ld.relaxed.gpu.global.u32 %0, [%1];" : "=r"(v) : "l"(p) : "memory");
    return v;
}
__device__ __forceinline__ void wait_count(const unsigned int* p, unsigned int target) {
    uint32_t n = 0;
    while (ld_relaxed_u32(p) < target) {
        __nanosleep(200);
        if (++n > SPIN_LIMIT) __trap();
    }
}
__device__ __forceinline__ void wait_front(const volatile int* front, int target) {
    uint32_t n = 0;
    while (*front < target) {
        __nanosleep(100);
        if (++n > SPIN_LIMIT) __trap();
    }
}

__global__ void __launch_bounds__(NTHREADS, 1)
gqa_fused_kernel(const __nv_bfloat16* __restrict__ x, const __nv_bfloat16* __restrict__ wq,
                 const __nv_bfloat16* __restrict__ wo, __nv_bfloat16* __restrict__ out,
                 const __grid_constant__ CUtensorMap tmK, const __grid_constant__ CUtensorMap tmV) {
    extern __shared__ uint8_t smem_raw[];
    const uint32_t raw_u32 = smem_u32(smem_raw);
    const uint32_t sb = (raw_u32 + 1023u) & ~1023u;
    uint8_t* sm = smem_raw + (sb - raw_u32);

    const int tid = threadIdx.x, warp = tid >> 5, lane = tid & 31;
    const int cta = blockIdx.x;
    const uint32_t bar_full = sb + SM_BAR, bar_empty = bar_full + 8 * STAGES, bar_wo = bar_empty + 8 * STAGES;
    volatile int* tidx = reinterpret_cast<volatile int*>(sm + SM_TIDX);
    volatile int* front = reinterpret_cast<volatile int*>(sm + SM_FRONT);
    volatile int* qflag = reinterpret_cast<volatile int*>(sm + SM_QFLAG);

    uint4 wv[9];
    uint32_t xa[9], xb[9];
    if (tid < 256) {
        if (cta < NJOB) {
            const int rg = tid >> 2, ch = tid & 3;
#pragma unroll
            for (int i = 0; i < 9; i++)
                wv[i] = ld_nc_v4(wq + (size_t)(rg + 64 * i) * (kHQ * kDH) + cta * 32 + ch * 8);
#pragma unroll
            for (int i = 0; i < 9; i++) {
                xa[i] = ld_nc_u16(x + rg + 64 * i);
                xb[i] = ld_nc_u16(x + kD + rg + 64 * i);
            }
        }
    } else if (tid == 256) {
        STAMP(0);
        asm volatile("prefetch.tensormap [%0];" ::"l"(&tmK) : "memory");
        asm volatile("prefetch.tensormap [%0];" ::"l"(&tmV) : "memory");
        for (int s = 0; s < STAGES; s++) {
            mbar_init(bar_full + 8 * s, 1);
            mbar_init(bar_empty + 8 * s, 4);
        }
        mbar_init(bar_wo, 1);
        *front = 0;
        for (int i = 0; i < kNG; i++) qflag[i] = 0;
        asm volatile("fence.mbarrier_init.release.cluster;" ::: "memory");
    }
    __syncthreads();

    if (warp == 8) {
        uint64_t pol = 0;
        int s = 0, it = 0, t = cta;
        uint32_t ph = 1;
        unsigned nxt = 0;
        bool done = false;
        auto issue = [&]() {
            if (it >= STAGES) mbar_wait(bar_empty + 8 * s, ph);
            const uint32_t fb = bar_full + 8 * s;
            if (t >= NTILES) {
                STAMP(3);
                tidx[s] = -1;
                *front = NTILES;
                mbar_arrive(fb);
                done = true;
                return;
            }
            tidx[s] = t;
            *front = t;
            mbar_expect_tx(fb, STAGE_BYTES);
            const uint32_t dk = sb + SM_RING + s * STAGE_BYTES, dv = dk + TILE_BYTES;
            const int row = t * TILE;
            tma2d(dk, &tmK, 0, row, fb, pol);
            tma2d(dk + HALF_BYTES, &tmK, 64, row, fb, pol);
            tma2d(dv, &tmV, 0, row, fb, pol);
            tma2d(dv + HALF_BYTES, &tmV, 64, row, fb, pol);
            ++it;
            if (it < STAGES) {
                t = it * NCTA + cta;
            } else {
                t = STAGES * NCTA + (int)nxt;
                if (t < NTILES) nxt = atomicAdd(&g_ctr, 1u);
            }
            if (++s == STAGES) { s = 0; ph ^= 1; }
        };
        if (lane == 0) {
            asm volatile("createpolicy.fractional.L2::evict_first.b64 %0, 1.0;" : "=l"(pol));
            for (int i = 0; i < EARLY_STAGES; i++) issue();
            nxt = atomicAdd(&g_ctr, 1u);
        }
        __syncwarp();
        if (cta < NJOB) named_bar(1, 288);
        if (lane == 0) {
            while (!done) issue();
        }
        return;
    }

    {
        float* red = reinterpret_cast<float*>(sm + SM_RED);
        if (cta < NJOB) {
            float acc[2][8];
#pragma unroll
            for (int c = 0; c < 8; c++) acc[0][c] = acc[1][c] = 0.f;
#pragma unroll
            for (int i = 0; i < 9; i++) {
                const float fa = __uint_as_float(xa[i] << 16), fb = __uint_as_float(xb[i] << 16);
                const uint32_t w4[4] = {wv[i].x, wv[i].y, wv[i].z, wv[i].w};
#pragma unroll
                for (int c = 0; c < 4; c++) {
                    const float lo = bf_lo(w4[c]), hi = bf_hi(w4[c]);
                    acc[0][2 * c] = fmaf(fa, lo, acc[0][2 * c]);
                    acc[0][2 * c + 1] = fmaf(fa, hi, acc[0][2 * c + 1]);
                    acc[1][2 * c] = fmaf(fb, lo, acc[1][2 * c]);
                    acc[1][2 * c + 1] = fmaf(fb, hi, acc[1][2 * c + 1]);
                }
            }
#pragma unroll
            for (int b = 0; b < 2; b++)
#pragma unroll
                for (int c = 0; c < 8; c++) {
                    float v = acc[b][c];
                    v += __shfl_xor_sync(0xffffffffu, v, 4);
                    v += __shfl_xor_sync(0xffffffffu, v, 8);
                    v += __shfl_xor_sync(0xffffffffu, v, 16);
                    acc[b][c] = v;
                }
            if (lane < 4) {
#pragma unroll
                for (int b = 0; b < 2; b++)
#pragma unroll
                    for (int c = 0; c < 8; c++) red[warp * 64 + b * 32 + lane * 8 + c] = acc[b][c];
            }
            named_bar(1, 288);
            if (tid == 0) STAMP(1);
            if (tid < 32) {
                float s0 = 0.f, s1 = 0.f;
#pragma unroll
                for (int w = 0; w < 8; w++) {
                    s0 += red[w * 64 + 2 * tid];
                    s1 += red[w * 64 + 2 * tid + 1];
                }
                uint32_t word = pack_bf16(s0, s1);
                if (word == 0u) word = 0x80008000u;
                st_relaxed_u32(&g_q[(tid >> 4) * 2048 + cta * 16 + (tid & 15)], word);
            }
        }
    }

    if (warp < 4) {
        const int g8 = lane >> 2, j = lane & 3, head = g8 & 1;
        const int l7 = lane & 7, mi = lane >> 3;
        uint32_t qf[8][2];
        float o[4][4];
        float m_run = -INFINITY, l_run = 0.f;
#pragma unroll
        for (int n = 0; n < 4; n++) o[n][0] = o[n][1] = o[n][2] = o[n][3] = 0.f;
#pragma unroll
        for (int k = 0; k < 8; k++) qf[k][0] = qf[k][1] = 0u;
        int cur_g = -1;
        int s = 0;
        uint32_t ph = 0, par = 0;
        const uint32_t koff = (uint32_t)((warp * KPW + l7) * 128);
        const uint32_t kc0 = (uint32_t)(((mi) ^ l7) << 4), kc1 = (uint32_t)(((4 + mi) ^ l7) << 4);
        const uint32_t voff = (uint32_t)(TILE_BYTES + (warp >> 1) * HALF_BYTES + ((mi & 1) * 8 + l7) * 128);
        const uint32_t vc0 = (uint32_t)((((warp & 1) * 4 + (mi >> 1)) ^ l7) << 4);
        const uint32_t vc1 = (uint32_t)((((warp & 1) * 4 + 2 + (mi >> 1)) ^ l7) << 4);

        while (true) {
            mbar_wait(bar_full + 8 * s, ph);
            const int t = tidx[s];
            const int g = t < 0 ? kNG : t / TPG;
            if (g != cur_g) {
                float lt = l_run;
                lt += __shfl_xor_sync(0xffffffffu, lt, 1);
                lt += __shfl_xor_sync(0xffffffffu, lt, 2);
                for (int gg = (cur_g < 0 ? 0 : cur_g); gg < g; gg++) {
                    const bool real = (gg == cur_g);
                    const int e = head * 4 + warp;
                    const int nsel = g8 >> 1;
                    float v0 = nsel == 0 ? o[0][0] : nsel == 1 ? o[1][0] : nsel == 2 ? o[2][0] : o[3][0];
                    float v1 = nsel == 0 ? o[0][1] : nsel == 1 ? o[1][1] : nsel == 2 ? o[2][1] : o[3][1];
                    if (!real) v0 = v1 = 0.f;
                    st_relaxed_v2(&g_po[gg][e][cta][nsel * 8 + 2 * j], make_uint2(enc(v0), enc(v1)));
                    if (lane < 8 && j == 0)
                        st_relaxed_v2(&g_pml[gg][e][cta], make_uint2(enc(real ? m_run : -INFINITY), enc(real ? lt : 0.f)));
                    if (lane == 0 && gg != kNG - 1) red_add(&g_done[gg * 32], 1u);
                }
                if (t < 0) { if (tid == 0) STAMP(4); break; }
                cur_g = g;
                m_run = -INFINITY;
                l_run = 0.f;
#pragma unroll
                for (int n = 0; n < 4; n++) o[n][0] = o[n][1] = 0.f;
                {
                    uint32_t n = 0;
                    while (qflag[g] == 0) {
                        if (++n > SPIN_LIMIT) __trap();
                    }
                    __threadfence_block();
                    if (tid == 0 && g == 0) STAMP(2);
                }
                const volatile uint32_t* qs = reinterpret_cast<const volatile uint32_t*>(sm + SM_Q) + g * 128 + head * 64 + j;
#pragma unroll
                for (int k = 0; k < 8; k++) {
                    qf[k][0] = qs[k * 8];
                    qf[k][1] = qs[k * 8 + 4];
                }
            }
            const uint32_t st = sb + SM_RING + s * STAGE_BYTES;
            float sc[NT_QK][2][4];
#pragma unroll
            for (int nt = 0; nt < NT_QK; nt++) {
#pragma unroll
                for (int h = 0; h < 2; h++) sc[nt][h][0] = sc[nt][h][1] = sc[nt][h][2] = sc[nt][h][3] = 0.f;
#pragma unroll
                for (int h = 0; h < 2; h++) {
                    uint32_t r0, r1, r2, r3;
                    ldsm4(st + koff + nt * 1024 + h * HALF_BYTES + kc0, r0, r1, r2, r3);
                    mma_bf16(sc[nt][h], qf[4 * h][0], qf[4 * h][1], r0, r1);
                    mma_bf16(sc[nt][h], qf[4 * h + 1][0], qf[4 * h + 1][1], r2, r3);
                    ldsm4(st + koff + nt * 1024 + h * HALF_BYTES + kc1, r0, r1, r2, r3);
                    mma_bf16(sc[nt][h], qf[4 * h + 2][0], qf[4 * h + 2][1], r0, r1);
                    mma_bf16(sc[nt][h], qf[4 * h + 3][0], qf[4 * h + 3][1], r2, r3);
                }
            }
            float2* sx = reinterpret_cast<float2*>(sm + SM_SX) + par * (TILE / 8) * 8;
            if (lane < 8) {
#pragma unroll
                for (int nt = 0; nt < NT_QK; nt++)
                    sx[(warp * NT_QK + nt) * 8 + lane] =
                        make_float2(sc[nt][0][0] + sc[nt][1][0], sc[nt][0][1] + sc[nt][1][1]);
            }
            named_bar(2, 128);
            float2 sv[TILE / 8];
#pragma unroll
            for (int n = 0; n < TILE / 8; n++) sv[n] = sx[n * 8 + head * 4 + j];
            float mx = fmaxf(sv[0].x, sv[0].y);
#pragma unroll
            for (int n = 1; n < TILE / 8; n++) mx = fmaxf(mx, fmaxf(sv[n].x, sv[n].y));
            mx = fmaxf(mx, __shfl_xor_sync(0xffffffffu, mx, 1));
            mx = fmaxf(mx, __shfl_xor_sync(0xffffffffu, mx, 2));
            const float m_new = fmaxf(m_run, mx);
            const float alpha = ex2((m_run - m_new) * kScaleLog2);
            const float mb = m_new * kScaleLog2;
            m_run = m_new;
            uint32_t pf[TILE / 8];
            float ls = 0.f;
#pragma unroll
            for (int n = 0; n < TILE / 8; n++) {
                const float p0 = ex2(fmaf(sv[n].x, kScaleLog2, -mb));
                const float p1 = ex2(fmaf(sv[n].y, kScaleLog2, -mb));
                ls += p0 + p1;
                pf[n] = pack_bf16(p0, p1);
            }
            l_run = fmaf(l_run, alpha, ls);
#pragma unroll
            for (int n = 0; n < 4; n++) {
                o[n][0] *= alpha;
                o[n][1] *= alpha;
            }
#pragma unroll
            for (int kb = 0; kb < NKB; kb++) {
                uint32_t r0, r1, r2, r3;
                ldsm4t(st + voff + kb * 2048 + vc0, r0, r1, r2, r3);
                mma_bf16(o[0], pf[2 * kb], pf[2 * kb + 1], r0, r1);
                mma_bf16(o[1], pf[2 * kb], pf[2 * kb + 1], r2, r3);
                ldsm4t(st + voff + kb * 2048 + vc1, r0, r1, r2, r3);
                mma_bf16(o[2], pf[2 * kb], pf[2 * kb + 1], r0, r1);
                mma_bf16(o[3], pf[2 * kb], pf[2 * kb + 1], r2, r3);
            }
            __syncwarp();
            if (lane == 0) mbar_arrive(bar_empty + 8 * s);
            par ^= 1;
            if (++s == STAGES) { s = 0; ph ^= 1; }
        }
        return;
    }

    const int et = tid - 128, ew = warp - 4;
    for (int g = ew; g < kNG; g += 4) {
        uint4 qv;
        uint32_t n = 0;
        while (true) {
            qv = ld_relaxed_v4(&g_q[g * 128 + lane * 4]);
            if (__all_sync(0xffffffffu, valid4(qv))) break;
            if (++n > SPIN_LIMIT) __trap();
        }
        *reinterpret_cast<uint4*>(sm + SM_Q + g * 512 + lane * 16) = qv;
        __threadfence_block();
        __syncwarp();
        if (lane == 0) qflag[g] = 1;
    }
    if (cta < NJOB) {
        const int hkv = cta >> 3, e = cta & 7;
        if (et == 0) {
            mbar_expect_tx(bar_wo, WO_BYTES);
            bulk_load(sb + SM_WO, wo + (size_t)cta * 32 * kD, WO_BYTES, bar_wo);
        }
        float* red = reinterpret_cast<float*>(sm + SM_RED);
        float* of = reinterpret_cast<float*>(sm + SM_OF);
        const int ch = et & 7, c0 = et >> 3;
        for (int b = 0; b < kB; b++) {
            const int g = b * kHKV + hkv;
            wait_front(front, (g + 1) * TPG);
            if (et == 0) STAMP(7 + 3 * b);
            if (g != kNG - 1) {
                if (et == 0) wait_count(&g_done[g * 32], 4 * NCTA);
                named_bar(3, 128);
            }
            uint4 ov[9];
            uint2 mv[5];
#pragma unroll
            for (int i = 0; i < 9; i++) {
                const bool use = (c0 + 16 * i) < NCTA;
                ov[i] = use ? make_uint4(0, 0, 0, 0) : make_uint4(0x80000000u, 0x80000000u, 0x80000000u, 0x80000000u);
            }
#pragma unroll
            for (int i = 0; i < 5; i++) {
                const bool use = (lane + 32 * i) < NCTA;
                mv[i] = use ? make_uint2(0, 0) : make_uint2(0xff800000u, 0x80000000u);
            }
            uint32_t n = 0;
            while (true) {
                bool ok = true;
#pragma unroll
                for (int i = 0; i < 5; i++)
                    if (mv[i].x == 0u || mv[i].y == 0u) mv[i] = ld_relaxed_v2(&g_pml[g][e][lane + 32 * i]);
#pragma unroll
                for (int i = 0; i < 9; i++)
                    if (!valid4(ov[i])) ov[i] = ld_relaxed_v4(&g_po[g][e][c0 + 16 * i][ch * 4]);
#pragma unroll
                for (int i = 0; i < 5; i++) ok = ok && mv[i].x != 0u && mv[i].y != 0u;
#pragma unroll
                for (int i = 0; i < 9; i++) ok = ok && valid4(ov[i]);
                if (__all_sync(0xffffffffu, ok)) break;
                if (++n > SPIN_LIMIT) __trap();
            }
            if (et == 0) STAMP(5 + 3 * b);
            float M = -INFINITY;
#pragma unroll
            for (int i = 0; i < 5; i++) M = fmaxf(M, __uint_as_float(mv[i].x));
#pragma unroll
            for (int d = 16; d > 0; d >>= 1) M = fmaxf(M, __shfl_xor_sync(0xffffffffu, M, d));
            float wc[5], L = 0.f;
#pragma unroll
            for (int i = 0; i < 5; i++) {
                wc[i] = ex2((__uint_as_float(mv[i].x) - M) * kScaleLog2);
                L = fmaf(wc[i], __uint_as_float(mv[i].y), L);
            }
#pragma unroll
            for (int d = 16; d > 0; d >>= 1) L += __shfl_xor_sync(0xffffffffu, L, d);
            float a0 = 0.f, a1 = 0.f, a2 = 0.f, a3 = 0.f;
#pragma unroll
            for (int i = 0; i < 9; i++) {
                const float w = __shfl_sync(0xffffffffu, wc[i >> 1], c0 + 16 * (i & 1));
                a0 = fmaf(w, __uint_as_float(ov[i].x), a0);
                a1 = fmaf(w, __uint_as_float(ov[i].y), a1);
                a2 = fmaf(w, __uint_as_float(ov[i].z), a2);
                a3 = fmaf(w, __uint_as_float(ov[i].w), a3);
            }
#pragma unroll
            for (int d = 8; d <= 16; d <<= 1) {
                a0 += __shfl_xor_sync(0xffffffffu, a0, d);
                a1 += __shfl_xor_sync(0xffffffffu, a1, d);
                a2 += __shfl_xor_sync(0xffffffffu, a2, d);
                a3 += __shfl_xor_sync(0xffffffffu, a3, d);
            }
            if (lane < 8) *reinterpret_cast<float4*>(red + ew * 32 + lane * 4) = make_float4(a0, a1, a2, a3);
            named_bar(3, 128);
            if (et < 32) {
                const float v = (red[et] + red[32 + et] + red[64 + et] + red[96 + et]) / L;
                of[et] = __bfloat162float(__float2bfloat16_rn(v));
            }
            if (b == 0) mbar_wait(bar_wo, 0);
            named_bar(3, 128);
            if (et < 72) {
                float acc[8];
#pragma unroll
                for (int c = 0; c < 8; c++) acc[c] = 0.f;
#pragma unroll 8
                for (int r = 0; r < 32; r++) {
                    const uint4 w = *reinterpret_cast<const uint4*>(sm + SM_WO + r * (kD * 2) + et * 16);
                    const float ov_ = of[r];
                    acc[0] = fmaf(ov_, bf_lo(w.x), acc[0]);
                    acc[1] = fmaf(ov_, bf_hi(w.x), acc[1]);
                    acc[2] = fmaf(ov_, bf_lo(w.y), acc[2]);
                    acc[3] = fmaf(ov_, bf_hi(w.y), acc[3]);
                    acc[4] = fmaf(ov_, bf_lo(w.z), acc[4]);
                    acc[5] = fmaf(ov_, bf_hi(w.z), acc[5]);
                    acc[6] = fmaf(ov_, bf_lo(w.w), acc[6]);
                    acc[7] = fmaf(ov_, bf_hi(w.w), acc[7]);
                }
                float* dst = &g_op[b][hkv][e][et * 8];
                st_relaxed_v4(dst, make_uint4(enc(acc[0]), enc(acc[1]), enc(acc[2]), enc(acc[3])));
                st_relaxed_v4(dst + 4, make_uint4(enc(acc[4]), enc(acc[5]), enc(acc[6]), enc(acc[7])));
            }
            if (lane == 0 && ew < 3 && g != kNG - 1) {
                red_add(&g_done2[g * 32], 1u);
                red_add(&g_done2[g * 32 + 16], 1u);
            }
            if (et == 0) STAMP(6 + 3 * b);
#pragma unroll
            for (int i = 0; i < 9; i++)
                if ((c0 + 16 * i) < NCTA) st_relaxed_v4(&g_po[g][e][c0 + 16 * i][ch * 4], make_uint4(0, 0, 0, 0));
            st_relaxed_v2(&g_pml[g][e][et], make_uint2(0, 0));
            if (et < NCTA - 128) st_relaxed_v2(&g_pml[g][e][128 + et], make_uint2(0, 0));
            named_bar(3, 128);
        }
        if (et < 32) st_relaxed_u32(&g_q[(et >> 4) * 2048 + cta * 16 + (et & 15)], 0u);
    } else {
        const int b = (cta - NJOB) >> 1, half = (cta - NJOB) & 1;
        if (ew < 3) {
            float a0 = 0.f, a1 = 0.f, a2 = 0.f, a3 = 0.f;
            const int col = half * 288 + et * 4;
            for (int hkv = 0; hkv < kHKV; hkv++) {
                const int g = b * kHKV + hkv;
                wait_front(front, (g + 1) * TPG);
                if (g != kNG - 1) {
                    if (et == 0) wait_count(&g_done2[g * 32 + half * 16], 24);
                    named_bar(3, 96);
                }
                if (et < 72) {
                    uint4 pv[8];
#pragma unroll
                    for (int i = 0; i < 8; i++) pv[i] = make_uint4(0, 0, 0, 0);
                    uint32_t n = 0;
                    while (true) {
                        bool ok = true;
#pragma unroll
                        for (int i = 0; i < 8; i++)
                            if (!valid4(pv[i])) pv[i] = ld_relaxed_v4(&g_op[b][hkv][i][col]);
#pragma unroll
                        for (int i = 0; i < 8; i++) ok = ok && valid4(pv[i]);
                        if (ok) break;
                        if (++n > SPIN_LIMIT) __trap();
                    }
#pragma unroll
                    for (int i = 0; i < 8; i++) {
                        a0 += __uint_as_float(pv[i].x);
                        a1 += __uint_as_float(pv[i].y);
                        a2 += __uint_as_float(pv[i].z);
                        a3 += __uint_as_float(pv[i].w);
                    }
                    if (hkv == kHKV - 1) {
                        uint2 r = make_uint2(pack_bf16(a0, a1), pack_bf16(a2, a3));
                        *reinterpret_cast<uint2*>(out + b * kD + col) = r;
                        if (et == 0) STAMP(11);
                        if (cta == NCTA - 1 && et == 0) st_relaxed_u32(&g_ctr, 0u);
                        if (et < kHKV) {
                            if (half == 0) st_relaxed_u32(&g_done[(b * kHKV + et) * 32], 0u);
                            st_relaxed_u32(&g_done2[(b * kHKV + et) * 32 + half * 16], 0u);
                        }
                    }
#pragma unroll
                    for (int i = 0; i < 8; i++) st_relaxed_v4(&g_op[b][hkv][i][col], make_uint4(0, 0, 0, 0));
                }
            }
        }
    }
}

__global__ void fb_qproj(const __nv_bfloat16* x, const __nv_bfloat16* wq) {
    const int idx = blockIdx.x * blockDim.x + threadIdx.x;
    const int b = idx / (kHQ * kDH), c = idx % (kHQ * kDH);
    float a = 0.f;
    for (int k = 0; k < kD; k++) a = fmaf(__bfloat162float(x[b * kD + k]), __bfloat162float(wq[(size_t)k * kHQ * kDH + c]), a);
    f_q[idx] = __bfloat162float(__float2bfloat16_rn(a));
}
__global__ void fb_attn(const __nv_bfloat16* K, const __nv_bfloat16* V) {
    __shared__ float sp[512];
    __shared__ float sred[128];
    const int split = blockIdx.x, bh = blockIdx.y, tid = threadIdx.x;
    const int b = bh / kHQ, h = bh % kHQ;
    const size_t base = ((size_t)(b * kHKV + h / 2) * kSK + split * 512) * kDH;
    const float* q = f_q + bh * kDH;
    float mx = -INFINITY;
    for (int k = tid; k < 512; k += 128) {
        float a = 0.f;
        for (int d = 0; d < kDH; d++) a = fmaf(q[d], __bfloat162float(K[base + (size_t)k * kDH + d]), a);
        sp[k] = a;
        mx = fmaxf(mx, a);
    }
    sred[tid] = mx;
    __syncthreads();
    for (int s = 64; s > 0; s >>= 1) { if (tid < s) sred[tid] = fmaxf(sred[tid], sred[tid + s]); __syncthreads(); }
    mx = sred[0];
    __syncthreads();
    float l = 0.f;
    for (int k = tid; k < 512; k += 128) { float p = exp2f((sp[k] - mx) * kScaleLog2); sp[k] = p; l += p; }
    sred[tid] = l;
    __syncthreads();
    for (int s = 64; s > 0; s >>= 1) { if (tid < s) sred[tid] += sred[tid + s]; __syncthreads(); }
    float a = 0.f;
    for (int k = 0; k < 512; k++) a = fmaf(sp[k], __bfloat162float(V[base + (size_t)k * kDH + tid]), a);
    f_po[bh][split][tid] = a;
    if (tid == 0) f_pml[bh][split] = make_float2(mx, sred[0]);
}
__global__ void fb_combine() {
    const int bh = blockIdx.x, tid = threadIdx.x;
    float M = -INFINITY;
    for (int s = 0; s < 64; s++) M = fmaxf(M, f_pml[bh][s].x);
    float L = 0.f, a = 0.f;
    for (int s = 0; s < 64; s++) {
        const float w = exp2f((f_pml[bh][s].x - M) * kScaleLog2);
        L = fmaf(w, f_pml[bh][s].y, L);
        a = fmaf(w, f_po[bh][s][tid], a);
    }
    f_o[bh * kDH + tid] = __bfloat162float(__float2bfloat16_rn(a / L));
}
__global__ void fb_oproj(const __nv_bfloat16* wo, __nv_bfloat16* out) {
    const int idx = blockIdx.x * blockDim.x + threadIdx.x;
    if (idx >= kB * kD) return;
    const int b = idx / kD, c = idx % kD;
    float a = 0.f;
    for (int k = 0; k < kHQ * kDH; k++) a = fmaf(f_o[b * kHQ * kDH + k], __bfloat162float(wo[(size_t)k * kD + c]), a);
    out[idx] = __float2bfloat16_rn(a);
}

typedef CUresult (*EncodeFn)(CUtensorMap*, CUtensorMapDataType, cuuint32_t, void*, const cuuint64_t*, const cuuint64_t*,
                             const cuuint32_t*, const cuuint32_t*, CUtensorMapInterleave, CUtensorMapSwizzle,
                             CUtensorMapL2promotion, CUtensorMapFloatOOBfill);

bool make_map(EncodeFn enc_fn, CUtensorMap* tm, const void* p) {
    cuuint64_t gd[2] = {(cuuint64_t)kDH, (cuuint64_t)kNG * kSK};
    cuuint64_t gs[1] = {(cuuint64_t)kDH * 2};
    cuuint32_t bx[2] = {64, (cuuint32_t)TILE};
    cuuint32_t es[2] = {1, 1};
    return enc_fn(tm, CU_TENSOR_MAP_DATA_TYPE_BFLOAT16, 2, const_cast<void*>(p), gd, gs, bx, es,
                  CU_TENSOR_MAP_INTERLEAVE_NONE, CU_TENSOR_MAP_SWIZZLE_128B, CU_TENSOR_MAP_L2_PROMOTION_L2_256B,
                  CU_TENSOR_MAP_FLOAT_OOB_FILL_NONE) == CUDA_SUCCESS;
}

}

extern "C" void kernel_launch(void* const* d_in, const int* in_sizes, int n_in, void* d_out, int out_size) {
    const __nv_bfloat16* x = (const __nv_bfloat16*)d_in[0];
    const __nv_bfloat16* K = (const __nv_bfloat16*)d_in[1];
    const __nv_bfloat16* V = (const __nv_bfloat16*)d_in[2];
    const __nv_bfloat16* wq = (const __nv_bfloat16*)d_in[3];
    const __nv_bfloat16* wo = (const __nv_bfloat16*)d_in[4];
    __nv_bfloat16* out = (__nv_bfloat16*)d_out;

    static int mode = -1;
    static EncodeFn enc_fn = nullptr;
    if (mode < 0) {
        mode = 0;
        int dev = 0, sms = 0, occ = 0;
        cudaGetDevice(&dev);
        cudaDeviceGetAttribute(&sms, cudaDevAttrMultiProcessorCount, dev);
        cudaDriverEntryPointQueryResult qr;
        void* fn = nullptr;
        if (cudaGetDriverEntryPoint("cuTensorMapEncodeTiled", &fn, cudaEnableDefault, &qr) == cudaSuccess && fn &&
            cudaFuncSetAttribute(gqa_fused_kernel, cudaFuncAttributeMaxDynamicSharedMemorySize, SMEM_BYTES) == cudaSuccess &&
            cudaOccupancyMaxActiveBlocksPerMultiprocessor(&occ, gqa_fused_kernel, NTHREADS, SMEM_BYTES) == cudaSuccess &&
            occ >= 1 && sms >= NCTA) {
            enc_fn = (EncodeFn)fn;
            mode = 1;
        }
        (void)cudaGetLastError();
    }
    if (mode == 1) {
        CUtensorMap tmK, tmV;
        if (make_map(enc_fn, &tmK, K) && make_map(enc_fn, &tmV, V)) {
            gqa_fused_kernel<<<NCTA, NTHREADS, SMEM_BYTES>>>(x, wq, wo, out, tmK, tmV);
            return;
        }
    }
    fb_qproj<<<32, 256>>>(x, wq);
    fb_attn<<<dim3(64, 64), 128>>>(K, V);
    fb_combine<<<64, 128>>>();
    fb_oproj<<<9, 128>>>(wo, out);
}
```

```cpp
#include <cuda_runtime.h>
#include <cuda_bf16.h>
#include <cuda.h>
#include <stdint.h>

namespace {

constexpr int kB = 2, kD = 576, kHQ = 32, kHKV = 16, kSK = 32768, kDH = 128;
constexpr int kNG = kB * kHKV;
#define CFG_TILE 32
#define CFG_STAGES 6
constexpr int TILE = CFG_TILE;
constexpr int STAGES = CFG_STAGES;
#define CFG_EARLY 3
constexpr int EARLY_STAGES = CFG_EARLY < STAGES ? CFG_EARLY : STAGES - 1;
constexpr int TPG = kSK / TILE;
constexpr int NTILES = kNG * TPG;
constexpr int NCTA = 132;
constexpr int NJOB = 128;
constexpr int TILE_BYTES = TILE * kDH * 2;
constexpr int HALF_BYTES = TILE_BYTES / 2;
constexpr int STAGE_BYTES = 2 * TILE_BYTES;
constexpr int KPW = TILE / 4;
constexpr int NT_QK = KPW / 8;
constexpr int NKB = TILE / 16;
constexpr int NTHREADS = 288;
constexpr int WO_ROW = kD * 2;
constexpr int WO_PITCH = WO_ROW + 16;
constexpr int WO_BYTES = 32 * WO_PITCH;

static_assert(TILE == 32 || TILE == 64 || TILE == 128, "tile");
static_assert(EARLY_STAGES >= 1, "the first issue() initialises the front marker");

constexpr int SM_RING = 0;
constexpr int SM_WO = SM_RING + STAGES * STAGE_BYTES;
constexpr int SM_Q = SM_WO + WO_BYTES;
constexpr int SM_SX = SM_Q + 16384;
constexpr int SM_RED = SM_SX + 2 * (TILE / 8) * 8 * 8;
constexpr int SM_OF = SM_RED + 8 * 64 * 4;
constexpr int SM_BAR = SM_OF + 128;
constexpr int SM_TIDX = SM_BAR + 8 * (2 * STAGES + 1);
constexpr int SM_FRONT = SM_TIDX + 4 * STAGES;
constexpr int SM_QFLAG = SM_FRONT + 16;
constexpr int SM_TOTAL = SM_QFLAG + 4 * kNG;
constexpr int SMEM_BYTES = SM_TOTAL + 1024;

__device__ unsigned int g_ctr;
__device__ __align__(16) uint32_t g_q[kB * kHQ * kDH / 2];
__device__ __align__(16) float g_po[kNG][8][NCTA][32];
__device__ __align__(16) float2 g_pml[kNG][8][NCTA];
__device__ __align__(16) float g_op[kB][kHKV][8][kD];
__device__ unsigned int g_done[kNG * 32];
__device__ unsigned int g_done2[kNG * 32];

#define STAMP(i) do { } while (0)
__device__ float f_q[kB * kHQ * kDH];
__device__ float f_po[kB * kHQ][64][kDH];
__device__ float2 f_pml[kB * kHQ][64];
__device__ float f_o[kB * kHQ * kDH];

__device__ __forceinline__ uint32_t smem_u32(const void* p) { return (uint32_t)__cvta_generic_to_shared(p); }
__device__ __forceinline__ void mbar_init(uint32_t bar, uint32_t cnt) {
    asm volatile("mbarrier.init.shared::cta.b64 [%0], %1;" ::"r"(bar), "r"(cnt) : "memory");
}
__device__ __forceinline__ void mbar_expect_tx(uint32_t bar, uint32_t bytes) {
    asm volatile("mbarrier.arrive.expect_tx.shared::cta.b64 _, [%0], %1;" ::"r"(bar), "r"(bytes) : "memory");
}
__device__ __forceinline__ void mbar_arrive(uint32_t bar) {
    asm volatile("mbarrier.arrive.shared::cta.b64 _, [%0];" ::"r"(bar) : "memory");
}
__device__ __forceinline__ bool mbar_try(uint32_t bar, uint32_t parity) {
    uint32_t ok;
    asm volatile(
        "{\n.reg .pred p;\nmbarrier.try_wait.parity.shared::cta.b64 p, [%1], %2;\nselp.u32 %0, 1, 0, p;\n}"
        : "=r"(ok) : "r"(bar), "r"(parity) : "memory");
    return ok != 0;
}
#define POLL_SLEEP_NS 0
#define LAST_HINT 0
#define TAIL_SLEEP_NS 40
constexpr uint32_t SPIN_LIMIT = 1u << 22;
__device__ __forceinline__ void mbar_wait(uint32_t bar, uint32_t parity) {
    uint32_t n = 0;
    while (!mbar_try(bar, parity)) {
        if (++n > SPIN_LIMIT) __trap();
    }
}
__device__ __forceinline__ void tma2d(uint32_t dst, const CUtensorMap* tm, int c0, int c1, uint32_t bar, uint64_t pol) {
    asm volatile(
        "cp.async.bulk.tensor.2d.shared::cluster.global.mbarrier::complete_tx::bytes.L2::cache_hint "
        "[%0], [%1, {%3, %4}], [%2], %5;" ::"r"(dst), "l"(tm), "r"(bar), "r"(c0), "r"(c1), "l"(pol) : "memory");
}
__device__ __forceinline__ void bulk_load(uint32_t dst, const void* src, uint32_t bytes, uint32_t bar) {
    asm volatile("cp.async.bulk.shared::cluster.global.mbarrier::complete_tx::bytes [%0], [%1], %2, [%3];"
                 ::"r"(dst), "l"(src), "r"(bytes), "r"(bar) : "memory");
}
__device__ __forceinline__ void named_bar(int id, int n) { asm volatile("bar.sync %0, %1;" ::"r"(id), "r"(n) : "memory"); }
__device__ __forceinline__ void ldsm4(uint32_t a, uint32_t& r0, uint32_t& r1, uint32_t& r2, uint32_t& r3) {
    asm volatile("ldmatrix.sync.aligned.m8n8.x4.shared.b16 {%0,%1,%2,%3}, [%4];"
                 : "=r"(r0), "=r"(r1), "=r"(r2), "=r"(r3) : "r"(a) : "memory");
}
__device__ __forceinline__ void ldsm4t(uint32_t a, uint32_t& r0, uint32_t& r1, uint32_t& r2, uint32_t& r3) {
    asm volatile("ldmatrix.sync.aligned.m8n8.x4.trans.shared.b16 {%0,%1,%2,%3}, [%4];"
                 : "=r"(r0), "=r"(r1), "=r"(r2), "=r"(r3) : "r"(a) : "memory");
}
__device__ __forceinline__ void mma_bf16(float (&c)[4], uint32_t a0, uint32_t a2, uint32_t b0, uint32_t b1) {
    asm volatile(
        "mma.sync.aligned.m16n8k16.row.col.f32.bf16.bf16.f32 {%0,%1,%2,%3}, {%4,%5,%6,%7}, {%8,%9}, {%0,%1,%2,%3};"
        : "+f"(c[0]), "+f"(c[1]), "+f"(c[2]), "+f"(c[3])
        : "r"(a0), "r"(0u), "r"(a2), "r"(0u), "r"(b0), "r"(b1));
}
__device__ __forceinline__ uint4 ld_relaxed_v4(const void* p) {
    uint4 v;
    asm volatile("ld.relaxed.gpu.global.v4.u32 {%0,%1,%2,%3}, [%4];" : "=r"(v.x), "=r"(v.y), "=r"(v.z), "=r"(v.w) : "l"(p) : "memory");
    return v;
}
__device__ __forceinline__ uint2 ld_relaxed_v2(const void* p) {
    uint2 v;
    asm volatile("ld.relaxed.gpu.global.v2.u32 {%0,%1}, [%2];" : "=r"(v.x), "=r"(v.y) : "l"(p) : "memory");
    return v;
}
__device__ __forceinline__ void st_relaxed_v4(void* p, uint4 v) {
    asm volatile("st.relaxed.gpu.global.v4.u32 [%0], {%1,%2,%3,%4};" ::"l"(p), "r"(v.x), "r"(v.y), "r"(v.z), "r"(v.w) : "memory");
}
__device__ __forceinline__ void st_relaxed_v2(void* p, uint2 v) {
    asm volatile("st.relaxed.gpu.global.v2.u32 [%0], {%1,%2};" ::"l"(p), "r"(v.x), "r"(v.y) : "memory");
}
__device__ __forceinline__ void st_relaxed_u32(void* p, uint32_t v) {
    asm volatile("st.relaxed.gpu.global.u32 [%0], %1;" ::"l"(p), "r"(v) : "memory");
}
__device__ __forceinline__ uint4 ld_nc_v4(const void* p) {
    uint4 v;
    asm volatile("ld.global.nc.L1::no_allocate.L2::256B.v4.u32 {%0,%1,%2,%3}, [%4];" : "=r"(v.x), "=r"(v.y), "=r"(v.z), "=r"(v.w) : "l"(p));
    return v;
}
__device__ __forceinline__ uint32_t ld_nc_u16(const void* p) {
    unsigned short v;
    asm volatile("ld.global.nc.u16 %0, [%1];" : "=h"(v) : "l"(p));
    return (uint32_t)v;
}
__device__ __forceinline__ uint32_t enc(float f) {
    uint32_t u = __float_as_uint(f);
    return u == 0u ? 0x80000000u : u;
}
__device__ __forceinline__ bool valid4(const uint4& v) { return v.x != 0u && v.y != 0u && v.z != 0u && v.w != 0u; }
__device__ __forceinline__ float bf_lo(uint32_t w) { return __uint_as_float(w << 16); }
__device__ __forceinline__ float bf_hi(uint32_t w) { return __uint_as_float(w & 0xffff0000u); }
__device__ __forceinline__ uint32_t pack_bf16(float lo, float hi) {
    uint32_t r;
    asm("cvt.rn.bf16x2.f32 %0, %1, %2;" : "=r"(r) : "f"(hi), "f"(lo));
    return r;
}
__device__ __forceinline__ float ex2(float x) {
    float y;
    asm("ex2.approx.ftz.f32 %0, %1;" : "=f"(y) : "f"(x));
    return y;
}

constexpr float kScale = 0.08838834764831845f;
constexpr float kLog2e = 1.4426950408889634f;
__device__ __forceinline__ float2 round_scores(float a, float b) {
    const uint32_t r1 = pack_bf16(a, b);
    const uint32_t r2 = pack_bf16(bf_lo(r1) * kScale, bf_hi(r1) * kScale);
    return make_float2(bf_lo(r2), bf_hi(r2));
}

__device__ __forceinline__ void red_add(unsigned int* p, unsigned int v) {
    asm volatile("red.relaxed.gpu.global.add.u32 [%0], %1;" ::"l"(p), "r"(v) : "memory");
}
__device__ __forceinline__ uint32_t ld_relaxed_u32(const void* p) {
    uint32_t v;
    asm volatile("ld.relaxed.gpu.global.u32 %0, [%1];" : "=r"(v) : "l"(p) : "memory");
    return v;
}
__device__ __forceinline__ void wait_count(const unsigned int* p, unsigned int target, unsigned ns) {
    uint32_t n = 0;
    while (ld_relaxed_u32(p) < target) {
        __nanosleep(ns);
        if (++n > SPIN_LIMIT) __trap();
    }
}
__device__ __forceinline__ void wait_front(const volatile int* front, int target) {
    uint32_t n = 0;
    while (*front < target) {
        __nanosleep(100);
        if (++n > SPIN_LIMIT) __trap();
    }
}

__global__ void __launch_bounds__(NTHREADS, 1)
gqa_fused_kernel(const __nv_bfloat16* __restrict__ x, const __nv_bfloat16* __restrict__ wq,
                 const __nv_bfloat16* __restrict__ wo, __nv_bfloat16* __restrict__ out,
                 const __grid_constant__ CUtensorMap tmK, const __grid_constant__ CUtensorMap tmV) {
    extern __shared__ uint8_t smem_raw[];
    const uint32_t raw_u32 = smem_u32(smem_raw);
    const uint32_t sb = (raw_u32 + 1023u) & ~1023u;
    uint8_t* sm = smem_raw + (sb - raw_u32);

    const int tid = threadIdx.x, warp = tid >> 5, lane = tid & 31;
    const int cta = blockIdx.x;
    const uint32_t bar_full = sb + SM_BAR, bar_empty = bar_full + 8 * STAGES, bar_wo = bar_empty + 8 * STAGES;
    volatile int* tidx = reinterpret_cast<volatile int*>(sm + SM_TIDX);
    volatile int* front = reinterpret_cast<volatile int*>(sm + SM_FRONT);
    volatile int* qflag = reinterpret_cast<volatile int*>(sm + SM_QFLAG);

    if (warp == 8) {
        uint64_t pol = 0;
        int s = 0, it = 0, t = cta;
        uint32_t ph = 1;
        unsigned nxt = 0;
        bool done = false;
        auto issue = [&]() {
            if (it >= STAGES) mbar_wait(bar_empty + 8 * s, ph);
            const uint32_t fb = bar_full + 8 * s;
            if (t >= NTILES) {
                STAMP(3);
                tidx[s] = -1;
                *front = NTILES;
                mbar_arrive(fb);
                done = true;
                return;
            }
            tidx[s] = t;
            *front = t;
            mbar_expect_tx(fb, STAGE_BYTES);
            const uint32_t dk = sb + SM_RING + s * STAGE_BYTES, dv = dk + TILE_BYTES;
            const int row = t * TILE;
            tma2d(dk, &tmK, 0, row, fb, pol);
            tma2d(dk + HALF_BYTES, &tmK, 64, row, fb, pol);
            tma2d(dv, &tmV, 0, row, fb, pol);
            tma2d(dv + HALF_BYTES, &tmV, 64, row, fb, pol);
            ++it;
            if (it < STAGES) {
                t = it * NCTA + cta;
            } else {
                t = STAGES * NCTA + (int)nxt;
                if (t < NTILES) nxt = atomicAdd(&g_ctr, 1u);
            }
            if (++s == STAGES) { s = 0; ph ^= 1; }
        };
        qflag[lane] = 0;
        if (lane == 0) {
            STAMP(0);
            asm volatile("prefetch.tensormap [%0];" ::"l"(&tmK) : "memory");
            asm volatile("prefetch.tensormap [%0];" ::"l"(&tmV) : "memory");
            for (int i = 0; i < STAGES; i++) {
                mbar_init(bar_full + 8 * i, 1);
                mbar_init(bar_empty + 8 * i, 4);
            }
            mbar_init(bar_wo, 1);
            asm volatile("fence.mbarrier_init.release.cluster;" ::: "memory");
            asm volatile("createpolicy.fractional.L2::evict_first.b64 %0, 1.0;" : "=l"(pol));
            for (int i = 0; i < EARLY_STAGES; i++) issue();
            nxt = atomicAdd(&g_ctr, 1u);
        }
        __syncwarp();
        named_bar(0, NTHREADS);
        if (cta < NJOB) named_bar(1, NTHREADS);
        if (lane == 0) {
            while (!done) issue();
        }
        return;
    }

    uint4 wv[9];
    uint32_t xa[9], xb[9];
    if (cta < NJOB) {
        const int rg = tid >> 2, ch = tid & 3;
#pragma unroll
        for (int i = 0; i < 9; i++)
            wv[i] = ld_nc_v4(wq + (size_t)(rg + 64 * i) * (kHQ * kDH) + cta * 32 + ch * 8);
#pragma unroll
        for (int i = 0; i < 9; i++) {
            xa[i] = ld_nc_u16(x + rg + 64 * i);
            xb[i] = ld_nc_u16(x + kD + rg + 64 * i);
        }
    }
    named_bar(0, NTHREADS);

    {
        float* red = reinterpret_cast<float*>(sm + SM_RED);
        if (cta < NJOB) {
            float acc[2][8];
#pragma unroll
            for (int c = 0; c < 8; c++) acc[0][c] = acc[1][c] = 0.f;
#pragma unroll
            for (int i = 0; i < 9; i++) {
                const float fa = __uint_as_float(xa[i] << 16), fb = __uint_as_float(xb[i] << 16);
                const uint32_t w4[4] = {wv[i].x, wv[i].y, wv[i].z, wv[i].w};
#pragma unroll
                for (int c = 0; c < 4; c++) {
                    const float lo = bf_lo(w4[c]), hi = bf_hi(w4[c]);
                    acc[0][2 * c] = fmaf(fa, lo, acc[0][2 * c]);
                    acc[0][2 * c + 1] = fmaf(fa, hi, acc[0][2 * c + 1]);
                    acc[1][2 * c] = fmaf(fb, lo, acc[1][2 * c]);
                    acc[1][2 * c + 1] = fmaf(fb, hi, acc[1][2 * c + 1]);
                }
            }
#pragma unroll
            for (int b = 0; b < 2; b++)
#pragma unroll
                for (int c = 0; c < 8; c++) {
                    float v = acc[b][c];
                    v += __shfl_xor_sync(0xffffffffu, v, 4);
                    v += __shfl_xor_sync(0xffffffffu, v, 8);
                    v += __shfl_xor_sync(0xffffffffu, v, 16);
                    acc[b][c] = v;
                }
            if (lane < 4) {
#pragma unroll
                for (int b = 0; b < 2; b++)
#pragma unroll
                    for (int c = 0; c < 8; c++) red[warp * 64 + b * 32 + lane * 8 + c] = acc[b][c];
            }
            named_bar(1, NTHREADS);
            if (tid == 0) STAMP(1);
            if (tid < 32) {
                float s0 = 0.f, s1 = 0.f;
#pragma unroll
                for (int w = 0; w < 8; w++) {
                    s0 += red[w * 64 + 2 * tid];
                    s1 += red[w * 64 + 2 * tid + 1];
                }
                uint32_t word = pack_bf16(s0, s1);
                if (word == 0u) word = 0x80008000u;
                st_relaxed_u32(&g_q[(tid >> 4) * 2048 + cta * 16 + (tid & 15)], word);
            }
        }
    }

    if (warp < 4) {
        const int g8 = lane >> 2, j = lane & 3, head = g8 & 1;
        const int l7 = lane & 7, mi = lane >> 3;
        uint32_t qf[8][2];
        float o[4][4];
        float m_run = -INFINITY, l_run = 0.f;
#pragma unroll
        for (int n = 0; n < 4; n++) o[n][0] = o[n][1] = o[n][2] = o[n][3] = 0.f;
#pragma unroll
        for (int k = 0; k < 8; k++) qf[k][0] = qf[k][1] = 0u;
        int cur_g = -1;
        int s = 0;
        uint32_t ph = 0, par = 0;
        const uint32_t koff = (uint32_t)((warp * KPW + l7) * 128);
        const uint32_t kc0 = (uint32_t)(((mi) ^ l7) << 4), kc1 = (uint32_t)(((4 + mi) ^ l7) << 4);
        const uint32_t voff = (uint32_t)(TILE_BYTES + (warp >> 1) * HALF_BYTES + ((mi & 1) * 8 + l7) * 128);
        const uint32_t vc0 = (uint32_t)((((warp & 1) * 4 + (mi >> 1)) ^ l7) << 4);
        const uint32_t vc1 = (uint32_t)((((warp & 1) * 4 + 2 + (mi >> 1)) ^ l7) << 4);

        while (true) {
            mbar_wait(bar_full + 8 * s, ph);
            const int t = tidx[s];
            const int g = t < 0 ? kNG : t / TPG;
            if (g != cur_g) {
                if (t < 0 && tid == 0) STAMP(21);
                float lt = l_run;
                lt += __shfl_xor_sync(0xffffffffu, lt, 1);
                lt += __shfl_xor_sync(0xffffffffu, lt, 2);
                for (int gg = (cur_g < 0 ? 0 : cur_g); gg < g; gg++) {
                    const bool real = (gg == cur_g);
                    if (!real) {
                        uint32_t n = 0;
                        while (qflag[gg] == 0) {
                            if (++n > SPIN_LIMIT) __trap();
                        }
                    }
                    const int e = head * 4 + warp;
                    const int nsel = g8 >> 1;
                    float v0 = nsel == 0 ? o[0][0] : nsel == 1 ? o[1][0] : nsel == 2 ? o[2][0] : o[3][0];
                    float v1 = nsel == 0 ? o[0][1] : nsel == 1 ? o[1][1] : nsel == 2 ? o[2][1] : o[3][1];
                    if (!real) v0 = v1 = 0.f;
                    st_relaxed_v2(&g_po[gg][e][cta][nsel * 8 + 2 * j], make_uint2(enc(v0), enc(v1)));
                    if (lane < 8 && j == 0)
                        st_relaxed_v2(&g_pml[gg][e][cta], make_uint2(enc(real ? m_run : -INFINITY), enc(real ? lt : 0.f)));
                    if (lane == 0 && (LAST_HINT || gg != kNG - 1)) red_add(&g_done[gg * 32], 1u);
                }
                if (t < 0) { if (tid == 0) STAMP(4); break; }
                cur_g = g;
                m_run = -INFINITY;
                l_run = 0.f;
#pragma unroll
                for (int n = 0; n < 4; n++) o[n][0] = o[n][1] = 0.f;
                {
                    uint32_t n = 0;
                    while (qflag[g] == 0) {
                        if (++n > SPIN_LIMIT) __trap();
                    }
                    __threadfence_block();
                    if (tid == 0 && g == 0) STAMP(2);
                }
                const volatile uint32_t* qs = reinterpret_cast<const volatile uint32_t*>(sm + SM_Q) + g * 128 + head * 64 + j;
#pragma unroll
                for (int k = 0; k < 8; k++) {
                    qf[k][0] = qs[k * 8];
                    qf[k][1] = qs[k * 8 + 4];
                }
            }
            const uint32_t st = sb + SM_RING + s * STAGE_BYTES;
            float sc[NT_QK][2][4];
#pragma unroll
            for (int nt = 0; nt < NT_QK; nt++) {
#pragma unroll
                for (int h = 0; h < 2; h++) sc[nt][h][0] = sc[nt][h][1] = sc[nt][h][2] = sc[nt][h][3] = 0.f;
#pragma unroll
                for (int h = 0; h < 2; h++) {
                    uint32_t r0, r1, r2, r3;
                    ldsm4(st + koff + nt * 1024 + h * HALF_BYTES + kc0, r0, r1, r2, r3);
                    mma_bf16(sc[nt][h], qf[4 * h][0], qf[4 * h][1], r0, r1);
                    mma_bf16(sc[nt][h], qf[4 * h + 1][0], qf[4 * h + 1][1], r2, r3);
                    ldsm4(st + koff + nt * 1024 + h * HALF_BYTES + kc1, r0, r1, r2, r3);
                    mma_bf16(sc[nt][h], qf[4 * h + 2][0], qf[4 * h + 2][1], r0, r1);
                    mma_bf16(sc[nt][h], qf[4 * h + 3][0], qf[4 * h + 3][1], r2, r3);
                }
            }
            float2* sx = reinterpret_cast<float2*>(sm + SM_SX) + par * (TILE / 8) * 8;
            if (lane < 8) {
#pragma unroll
                for (int nt = 0; nt < NT_QK; nt++)
                    sx[(warp * NT_QK + nt) * 8 + lane] =
                        round_scores(sc[nt][0][0] + sc[nt][1][0], sc[nt][0][1] + sc[nt][1][1]);
            }
            named_bar(2, 128);
            float2 sv[TILE / 8];
#pragma unroll
            for (int n = 0; n < TILE / 8; n++) sv[n] = sx[n * 8 + head * 4 + j];
            float mx = fmaxf(sv[0].x, sv[0].y);
#pragma unroll
            for (int n = 1; n < TILE / 8; n++) mx = fmaxf(mx, fmaxf(sv[n].x, sv[n].y));
            mx = fmaxf(mx, __shfl_xor_sync(0xffffffffu, mx, 1));
            mx = fmaxf(mx, __shfl_xor_sync(0xffffffffu, mx, 2));
            const float m_new = fmaxf(m_run, mx);
            const float alpha = ex2((m_run - m_new) * kLog2e);
            const float mb = m_new * kLog2e;
            m_run = m_new;
            uint32_t pf[TILE / 8];
            float ls = 0.f;
#pragma unroll
            for (int n = 0; n < TILE / 8; n++) {
                const float p0 = ex2(fmaf(sv[n].x, kLog2e, -mb));
                const float p1 = ex2(fmaf(sv[n].y, kLog2e, -mb));
                ls += p0 + p1;
                pf[n] = pack_bf16(p0, p1);
            }
            l_run = fmaf(l_run, alpha, ls);
#pragma unroll
            for (int n = 0; n < 4; n++) {
                o[n][0] *= alpha;
                o[n][1] *= alpha;
            }
#pragma unroll
            for (int kb = 0; kb < NKB; kb++) {
                uint32_t r0, r1, r2, r3;
                ldsm4t(st + voff + kb * 2048 + vc0, r0, r1, r2, r3);
                mma_bf16(o[0], pf[2 * kb], pf[2 * kb + 1], r0, r1);
                mma_bf16(o[1], pf[2 * kb], pf[2 * kb + 1], r2, r3);
                ldsm4t(st + voff + kb * 2048 + vc1, r0, r1, r2, r3);
                mma_bf16(o[2], pf[2 * kb], pf[2 * kb + 1], r0, r1);
                mma_bf16(o[3], pf[2 * kb], pf[2 * kb + 1], r2, r3);
            }
            __syncwarp();
            if (lane == 0) mbar_arrive(bar_empty + 8 * s);
            par ^= 1;
            if (++s == STAGES) { s = 0; ph ^= 1; }
        }
        return;
    }

    const int et = tid - 128, ew = warp - 4;
    for (int g = ew; g < kNG; g += 4) {
        uint4 qv;
        uint32_t n = 0;
        while (true) {
            qv = ld_relaxed_v4(&g_q[g * 128 + lane * 4]);
            if (__all_sync(0xffffffffu, valid4(qv))) break;
            if (++n > SPIN_LIMIT) __trap();
        }
        *reinterpret_cast<uint4*>(sm + SM_Q + g * 512 + lane * 16) = qv;
        __threadfence_block();
        __syncwarp();
        if (lane == 0) qflag[g] = 1;
    }
    if (cta < NJOB) {
        const int hkv = cta >> 3, e = cta & 7;
        if (ew == 0) {
            if (lane == 0) mbar_expect_tx(bar_wo, 32 * WO_ROW);
            __syncwarp();
            bulk_load(sb + SM_WO + lane * WO_PITCH, wo + (size_t)(cta * 32 + lane) * kD, WO_ROW, bar_wo);
        }
        float* red = reinterpret_cast<float*>(sm + SM_RED);
        const int ch = et & 7, c0 = et >> 3, g8 = lane >> 2, j = lane & 3;
        for (int b = 0; b < kB; b++) {
            const int g = b * kHKV + hkv;
            wait_front(front, (g + 1) * TPG);
            if (et == 0) STAMP(7 + 3 * b);
            if (LAST_HINT || g != kNG - 1) {
                if (et == 0) wait_count(&g_done[g * 32], 4 * NCTA, g == kNG - 1 ? TAIL_SLEEP_NS : 200);
                named_bar(3, 128);
            }
            uint4 ov[9];
            uint2 mv[5];
#pragma unroll
            for (int i = 0; i < 9; i++) {
                const bool use = (c0 + 16 * i) < NCTA;
                ov[i] = use ? make_uint4(0, 0, 0, 0) : make_uint4(0x80000000u, 0x80000000u, 0x80000000u, 0x80000000u);
            }
#pragma unroll
            for (int i = 0; i < 5; i++) {
                const bool use = (lane + 32 * i) < NCTA;
                mv[i] = use ? make_uint2(0, 0) : make_uint2(0xff800000u, 0x80000000u);
            }
            uint32_t n = 0;
            while (true) {
                bool ok = true;
#pragma unroll
                for (int i = 0; i < 5; i++)
                    if (mv[i].x == 0u || mv[i].y == 0u) mv[i] = ld_relaxed_v2(&g_pml[g][e][lane + 32 * i]);
#pragma unroll
                for (int i = 0; i < 9; i++)
                    if (!valid4(ov[i])) ov[i] = ld_relaxed_v4(&g_po[g][e][c0 + 16 * i][ch * 4]);
#pragma unroll
                for (int i = 0; i < 5; i++) ok = ok && mv[i].x != 0u && mv[i].y != 0u;
#pragma unroll
                for (int i = 0; i < 9; i++) ok = ok && valid4(ov[i]);
                if (__all_sync(0xffffffffu, ok)) break;
                if (POLL_SLEEP_NS) __nanosleep(POLL_SLEEP_NS);
                if (++n > SPIN_LIMIT) __trap();
            }
            if (et == 0) STAMP(5 + 3 * b);
            if (lane == 0 && b == 1) STAMP(16 + ew);
            float M = -INFINITY;
#pragma unroll
            for (int i = 0; i < 5; i++) M = fmaxf(M, __uint_as_float(mv[i].x));
#pragma unroll
            for (int d = 16; d > 0; d >>= 1) M = fmaxf(M, __shfl_xor_sync(0xffffffffu, M, d));
            float wc[5], L = 0.f;
#pragma unroll
            for (int i = 0; i < 5; i++) {
                wc[i] = ex2((__uint_as_float(mv[i].x) - M) * kLog2e);
                L = fmaf(wc[i], __uint_as_float(mv[i].y), L);
            }
#pragma unroll
            for (int d = 16; d > 0; d >>= 1) L += __shfl_xor_sync(0xffffffffu, L, d);
            float a0 = 0.f, a1 = 0.f, a2 = 0.f, a3 = 0.f;
#pragma unroll
            for (int i = 0; i < 9; i++) {
                const float w = __shfl_sync(0xffffffffu, wc[i >> 1], c0 + 16 * (i & 1));
                a0 = fmaf(w, __uint_as_float(ov[i].x), a0);
                a1 = fmaf(w, __uint_as_float(ov[i].y), a1);
                a2 = fmaf(w, __uint_as_float(ov[i].z), a2);
                a3 = fmaf(w, __uint_as_float(ov[i].w), a3);
            }
#pragma unroll
            for (int d = 8; d <= 16; d <<= 1) {
                a0 += __shfl_xor_sync(0xffffffffu, a0, d);
                a1 += __shfl_xor_sync(0xffffffffu, a1, d);
                a2 += __shfl_xor_sync(0xffffffffu, a2, d);
                a3 += __shfl_xor_sync(0xffffffffu, a3, d);
            }
            if (lane < 8) *reinterpret_cast<float4*>(red + ew * 32 + lane * 4) = make_float4(a0, a1, a2, a3);
            if (b == 0) mbar_wait(bar_wo, 0);
            named_bar(3, 128);
            if (et == 0 && b == 1) STAMP(20);
            const float rl = 1.0f / L;
            uint32_t af[4];
#pragma unroll
            for (int k = 0; k < 4; k++) {
                float2 v = *reinterpret_cast<const float2*>(red + k * 8 + 2 * j);
#pragma unroll
                for (int w = 1; w < 4; w++) {
                    const float2 u = *reinterpret_cast<const float2*>(red + w * 32 + k * 8 + 2 * j);
                    v.x += u.x;
                    v.y += u.y;
                }
                af[k] = pack_bf16(v.x * rl, v.y * rl);
            }
            {
                const uint32_t wbase = sb + SM_WO + lane * WO_PITCH + ew * 288;
                float* dst = &g_op[b][hkv][e][ew * 144 + g8 * 8 + 2 * j];
#pragma unroll
                for (int bt = 0; bt < 3; bt++) {
                    float r0 = 0.f, r1 = 0.f;
#pragma unroll
                    for (int tt = 0; tt < (bt < 2 ? 8 : 2); tt++) {
                        uint32_t b0, b1, b2, b3;
                        ldsm4t(wbase + (bt * 8 + tt) * 16, b0, b1, b2, b3);
                        float c[4] = {0.f, 0.f, 0.f, 0.f};
                        mma_bf16(c, af[0], af[1], b0, b1);
                        mma_bf16(c, af[2], af[3], b2, b3);
                        if (g8 == tt) { r0 = c[0]; r1 = c[1]; }
                    }
                    if (bt < 2 || g8 < 2) st_relaxed_v2(dst + bt * 64, make_uint2(enc(r0), enc(r1)));
                }
            }
            if (lane == 0 && (LAST_HINT || g != kNG - 1)) red_add(&g_done2[g * 32 + (ew >> 1) * 16], 1u);
            if (et == 0) STAMP(6 + 3 * b);
#pragma unroll
            for (int i = 0; i < 9; i++)
                if ((c0 + 16 * i) < NCTA) st_relaxed_v4(&g_po[g][e][c0 + 16 * i][ch * 4], make_uint4(0, 0, 0, 0));
            st_relaxed_v2(&g_pml[g][e][et], make_uint2(0, 0));
            if (et < NCTA - 128) st_relaxed_v2(&g_pml[g][e][128 + et], make_uint2(0, 0));
            named_bar(3, 128);
        }
        if (et < 32) st_relaxed_u32(&g_q[(et >> 4) * 2048 + cta * 16 + (et & 15)], 0u);
    } else {
        const int b = (cta - NJOB) >> 1, half = (cta - NJOB) & 1;
        if (ew < 3) {
            float a0 = 0.f, a1 = 0.f, a2 = 0.f, a3 = 0.f;
            const int col = half * 288 + et * 4;
            for (int hkv = 0; hkv < kHKV; hkv++) {
                const int g = b * kHKV + hkv;
                wait_front(front, (g + 1) * TPG);
                if (LAST_HINT || g != kNG - 1) {
                    if (et == 0) wait_count(&g_done2[g * 32 + half * 16], 16, g == kNG - 1 ? TAIL_SLEEP_NS : 200);
                    named_bar(3, 96);
                }
                if (et < 72) {
                    uint4 pv[8];
#pragma unroll
                    for (int i = 0; i < 8; i++) pv[i] = make_uint4(0, 0, 0, 0);
                    uint32_t n = 0;
                    while (true) {
                        bool ok = true;
#pragma unroll
                        for (int i = 0; i < 8; i++)
                            if (!valid4(pv[i])) pv[i] = ld_relaxed_v4(&g_op[b][hkv][i][col]);
#pragma unroll
                        for (int i = 0; i < 8; i++) ok = ok && valid4(pv[i]);
                        if (ok) break;
                        if (POLL_SLEEP_NS) __nanosleep(POLL_SLEEP_NS);
                        if (++n > SPIN_LIMIT) __trap();
                    }
                    if (hkv == kHKV - 1 && lane == 0) STAMP(22 + ew);
#pragma unroll
                    for (int i = 0; i < 8; i++) {
                        a0 += __uint_as_float(pv[i].x);
                        a1 += __uint_as_float(pv[i].y);
                        a2 += __uint_as_float(pv[i].z);
                        a3 += __uint_as_float(pv[i].w);
                    }
                    if (hkv == kHKV - 1) {
                        uint2 r = make_uint2(pack_bf16(a0, a1), pack_bf16(a2, a3));
                        *reinterpret_cast<uint2*>(out + b * kD + col) = r;
                        if (et == 0) STAMP(11);
                        if (cta == NCTA - 1 && et == 0) st_relaxed_u32(&g_ctr, 0u);
                        if (et < kHKV) {
                            if (half == 0) st_relaxed_u32(&g_done[(b * kHKV + et) * 32], 0u);
                            st_relaxed_u32(&g_done2[(b * kHKV + et) * 32 + half * 16], 0u);
                        }
                    }
#pragma unroll
                    for (int i = 0; i < 8; i++) st_relaxed_v4(&g_op[b][hkv][i][col], make_uint4(0, 0, 0, 0));
                }
            }
        }
    }
}

__global__ void fb_qproj(const __nv_bfloat16* x, const __nv_bfloat16* wq) {
    const int idx = blockIdx.x * blockDim.x + threadIdx.x;
    const int b = idx / (kHQ * kDH), c = idx % (kHQ * kDH);
    float a = 0.f;
    for (int k = 0; k < kD; k++) a = fmaf(__bfloat162float(x[b * kD + k]), __bfloat162float(wq[(size_t)k * kHQ * kDH + c]), a);
    f_q[idx] = __bfloat162float(__float2bfloat16_rn(a));
}
__global__ void fb_attn(const __nv_bfloat16* K, const __nv_bfloat16* V) {
    __shared__ float sp[512];
    __shared__ float sred[128];
    const int split = blockIdx.x, bh = blockIdx.y, tid = threadIdx.x;
    const int b = bh / kHQ, h = bh % kHQ;
    const size_t base = ((size_t)(b * kHKV + h / 2) * kSK + split * 512) * kDH;
    const float* q = f_q + bh * kDH;
    float mx = -INFINITY;
    for (int k = tid; k < 512; k += 128) {
        float a = 0.f;
        for (int d = 0; d < kDH; d++) a = fmaf(q[d], __bfloat162float(K[base + (size_t)k * kDH + d]), a);
        a = round_scores(a, 0.f).x;
        sp[k] = a;
        mx = fmaxf(mx, a);
    }
    sred[tid] = mx;
    __syncthreads();
    for (int s = 64; s > 0; s >>= 1) { if (tid < s) sred[tid] = fmaxf(sred[tid], sred[tid + s]); __syncthreads(); }
    mx = sred[0];
    __syncthreads();
    float l = 0.f;
    for (int k = tid; k < 512; k += 128) { float p = exp2f((sp[k] - mx) * kLog2e); sp[k] = p; l += p; }
    sred[tid] = l;
    __syncthreads();
    for (int s = 64; s > 0; s >>= 1) { if (tid < s) sred[tid] += sred[tid + s]; __syncthreads(); }
    float a = 0.f;
    for (int k = 0; k < 512; k++) a = fmaf(sp[k], __bfloat162float(V[base + (size_t)k * kDH + tid]), a);
    f_po[bh][split][tid] = a;
    if (tid == 0) f_pml[bh][split] = make_float2(mx, sred[0]);
}
__global__ void fb_combine() {
    const int bh = blockIdx.x, tid = threadIdx.x;
    float M = -INFINITY;
    for (int s = 0; s < 64; s++) M = fmaxf(M, f_pml[bh][s].x);
    float L = 0.f, a = 0.f;
    for (int s = 0; s < 64; s++) {
        const float w = exp2f((f_pml[bh][s].x - M) * kLog2e);
        L = fmaf(w, f_pml[bh][s].y, L);
        a = fmaf(w, f_po[bh][s][tid], a);
    }
    f_o[bh * kDH + tid] = __bfloat162float(__float2bfloat16_rn(a / L));
}
__global__ void fb_oproj(const __nv_bfloat16* wo, __nv_bfloat16* out) {
    const int idx = blockIdx.x * blockDim.x + threadIdx.x;
    if (idx >= kB * kD) return;
    const int b = idx / kD, c = idx % kD;
    float a = 0.f;
    for (int k = 0; k < kHQ * kDH; k++) a = fmaf(f_o[b * kHQ * kDH + k], __bfloat162float(wo[(size_t)k * kD + c]), a);
    out[idx] = __float2bfloat16_rn(a);
}

typedef CUresult (*EncodeFn)(CUtensorMap*, CUtensorMapDataType, cuuint32_t, void*, const cuuint64_t*, const cuuint64_t*,
                             const cuuint32_t*, const cuuint32_t*, CUtensorMapInterleave, CUtensorMapSwizzle,
                             CUtensorMapL2promotion, CUtensorMapFloatOOBfill);

bool make_map(EncodeFn enc_fn, CUtensorMap* tm, const void* p) {
    cuuint64_t gd[2] = {(cuuint64_t)kDH, (cuuint64_t)kNG * kSK};
    cuuint64_t gs[1] = {(cuuint64_t)kDH * 2};
    cuuint32_t bx[2] = {64, (cuuint32_t)TILE};
    cuuint32_t es[2] = {1, 1};
    return enc_fn(tm, CU_TENSOR_MAP_DATA_TYPE_BFLOAT16, 2, const_cast<void*>(p), gd, gs, bx, es,
                  CU_TENSOR_MAP_INTERLEAVE_NONE, CU_TENSOR_MAP_SWIZZLE_128B, CU_TENSOR_MAP_L2_PROMOTION_L2_256B,
                  CU_TENSOR_MAP_FLOAT_OOB_FILL_NONE) == CUDA_SUCCESS;
}

}

extern "C" void kernel_launch(void* const* d_in, const int* in_sizes, int n_in, void* d_out, int out_size) {
    const __nv_bfloat16* x = (const __nv_bfloat16*)d_in[0];
    const __nv_bfloat16* K = (const __nv_bfloat16*)d_in[1];
    const __nv_bfloat16* V = (const __nv_bfloat16*)d_in[2];
    const __nv_bfloat16* wq = (const __nv_bfloat16*)d_in[3];
    const __nv_bfloat16* wo = (const __nv_bfloat16*)d_in[4];
    __nv_bfloat16* out = (__nv_bfloat16*)d_out;

    static int mode = -1;
    static EncodeFn enc_fn = nullptr;
    if (mode < 0) {
        mode = 0;
        int dev = 0, sms = 0, occ = 0;
        cudaGetDevice(&dev);
        cudaDeviceGetAttribute(&sms, cudaDevAttrMultiProcessorCount, dev);
        cudaDriverEntryPointQueryResult qr;
        void* fn = nullptr;
        if (cudaGetDriverEntryPoint("cuTensorMapEncodeTiled", &fn, cudaEnableDefault, &qr) == cudaSuccess && fn &&
            cudaFuncSetAttribute(gqa_fused_kernel, cudaFuncAttributeMaxDynamicSharedMemorySize, SMEM_BYTES) == cudaSuccess &&
            cudaOccupancyMaxActiveBlocksPerMultiprocessor(&occ, gqa_fused_kernel, NTHREADS, SMEM_BYTES) == cudaSuccess &&
            occ >= 1 && sms >= NCTA) {
            enc_fn = (EncodeFn)fn;
            mode = 1;
        }
        (void)cudaGetLastError();
    }
    if (mode == 1) {
        CUtensorMap tmK, tmV;
        if (make_map(enc_fn, &tmK, K) && make_map(enc_fn, &tmV, V)) {
            gqa_fused_kernel<<<NCTA, NTHREADS, SMEM_BYTES>>>(x, wq, wo, out, tmK, tmV);
            return;
        }
    }
    fb_qproj<<<32, 256>>>(x, wq);
    fb_attn<<<dim3(64, 64), 128>>>(K, V);
    fb_combine<<<64, 128>>>();
    fb_oproj<<<9, 128>>>(wo, out);
}
```

```cpp
#include <cuda_runtime.h>
#include <cuda_bf16.h>
#include <cuda.h>
#include <stdint.h>

namespace {

constexpr int kB = 2, kD = 576, kHQ = 32, kHKV = 16, kSK = 32768, kDH = 128;
constexpr int kNG = kB * kHKV;
#define CFG_TILE 32
#define CFG_STAGES 6
constexpr int TILE = CFG_TILE;
constexpr int STAGES = CFG_STAGES;
#define CFG_EARLY 3
constexpr int EARLY_STAGES = CFG_EARLY < STAGES ? CFG_EARLY : STAGES - 1;
constexpr int TPG = kSK / TILE;
constexpr int NTILES = kNG * TPG;
constexpr int NCTA = 132;
constexpr int NJOB = 128;
constexpr int TILE_BYTES = TILE * kDH * 2;
constexpr int HALF_BYTES = TILE_BYTES / 2;
constexpr int STAGE_BYTES = 2 * TILE_BYTES;
constexpr int KPW = TILE / 4;
constexpr int NT_QK = KPW / 8;
constexpr int NKB = TILE / 16;
constexpr int NTHREADS = 288;
constexpr int WO_ROW = kD * 2;
constexpr int WO_PITCH = WO_ROW + 16;
constexpr int WO_BYTES = 32 * WO_PITCH;

static_assert(TILE == 32 || TILE == 64 || TILE == 128, "tile");
static_assert(EARLY_STAGES >= 1, "the first issue() initialises the front marker");

constexpr int SM_RING = 0;
constexpr int SM_WO = SM_RING + STAGES * STAGE_BYTES;
constexpr int SM_Q = SM_WO + WO_BYTES;
constexpr int SM_SX = SM_Q + 16384;
constexpr int SM_RED = SM_SX + 2 * (TILE / 8) * 8 * 8;
constexpr int SM_BAR = SM_RED + 8 * 64 * 4;
constexpr int SM_TIDX = SM_BAR + 8 * (2 * STAGES + 1);
constexpr int SM_FRONT = SM_TIDX + 4 * STAGES;
constexpr int SM_QFLAG = SM_FRONT + 16;
constexpr int SM_TOTAL = SM_QFLAG + 4 * kNG;
constexpr int SMEM_BYTES = SM_TOTAL + 1024;

__device__ unsigned int g_ctr;
__device__ __align__(16) uint32_t g_q[kB * kHQ * kDH / 2];
__device__ __align__(16) float g_po[kNG][8][NCTA][32];
__device__ __align__(16) float2 g_pml[kNG][8][NCTA];
__device__ __align__(16) float g_op[kB][kHKV][8][kD];
__device__ unsigned int g_done[kNG * 32];
__device__ unsigned int g_done2[kNG * 32];

#define STAMP(i) do { } while (0)
__device__ float f_q[kB * kHQ * kDH];
__device__ float f_po[kB * kHQ][64][kDH];
__device__ float2 f_pml[kB * kHQ][64];
__device__ float f_o[kB * kHQ * kDH];

__device__ __forceinline__ uint32_t smem_u32(const void* p) { return (uint32_t)__cvta_generic_to_shared(p); }
__device__ __forceinline__ void mbar_init(uint32_t bar, uint32_t cnt) {
    asm volatile("mbarrier.init.shared::cta.b64 [%0], %1;" ::"r"(bar), "r"(cnt) : "memory");
}
__device__ __forceinline__ void mbar_expect_tx(uint32_t bar, uint32_t bytes) {
    asm volatile("mbarrier.arrive.expect_tx.shared::cta.b64 _, [%0], %1;" ::"r"(bar), "r"(bytes) : "memory");
}
__device__ __forceinline__ void mbar_arrive(uint32_t bar) {
    asm volatile("mbarrier.arrive.shared::cta.b64 _, [%0];" ::"r"(bar) : "memory");
}
__device__ __forceinline__ bool mbar_try(uint32_t bar, uint32_t parity) {
    uint32_t ok;
    asm volatile(
        "{\n.reg .pred p;\nmbarrier.try_wait.parity.shared::cta.b64 p, [%1], %2;\nselp.u32 %0, 1, 0, p;\n}"
        : "=r"(ok) : "r"(bar), "r"(parity) : "memory");
    return ok != 0;
}
constexpr uint32_t SPIN_LIMIT = 1u << 22;
__device__ __forceinline__ void mbar_wait(uint32_t bar, uint32_t parity) {
    uint32_t n = 0;
    while (!mbar_try(bar, parity)) {
        if (++n > SPIN_LIMIT) __trap();
    }
}
__device__ __forceinline__ void tma2d(uint32_t dst, const CUtensorMap* tm, int c0, int c1, uint32_t bar, uint64_t pol) {
    asm volatile(
        "cp.async.bulk.tensor.2d.shared::cluster.global.mbarrier::complete_tx::bytes.L2::cache_hint "
        "[%0], [%1, {%3, %4}], [%2], %5;" ::"r"(dst), "l"(tm), "r"(bar), "r"(c0), "r"(c1), "l"(pol) : "memory");
}
__device__ __forceinline__ void bulk_load(uint32_t dst, const void* src, uint32_t bytes, uint32_t bar) {
    asm volatile("cp.async.bulk.shared::cluster.global.mbarrier::complete_tx::bytes [%0], [%1], %2, [%3];"
                 ::"r"(dst), "l"(src), "r"(bytes), "r"(bar) : "memory");
}
__device__ __forceinline__ void named_bar(int id, int n) { asm volatile("bar.sync %0, %1;" ::"r"(id), "r"(n) : "memory"); }
__device__ __forceinline__ void ldsm4(uint32_t a, uint32_t& r0, uint32_t& r1, uint32_t& r2, uint32_t& r3) {
    asm volatile("ldmatrix.sync.aligned.m8n8.x4.shared.b16 {%0,%1,%2,%3}, [%4];"
                 : "=r"(r0), "=r"(r1), "=r"(r2), "=r"(r3) : "r"(a) : "memory");
}
__device__ __forceinline__ void ldsm4t(uint32_t a, uint32_t& r0, uint32_t& r1, uint32_t& r2, uint32_t& r3) {
    asm volatile("ldmatrix.sync.aligned.m8n8.x4.trans.shared.b16 {%0,%1,%2,%3}, [%4];"
                 : "=r"(r0), "=r"(r1), "=r"(r2), "=r"(r3) : "r"(a) : "memory");
}
__device__ __forceinline__ void mma_bf16(float (&c)[4], uint32_t a0, uint32_t a2, uint32_t b0, uint32_t b1) {
    asm volatile(
        "mma.sync.aligned.m16n8k16.row.col.f32.bf16.bf16.f32 {%0,%1,%2,%3}, {%4,%5,%6,%7}, {%8,%9}, {%0,%1,%2,%3};"
        : "+f"(c[0]), "+f"(c[1]), "+f"(c[2]), "+f"(c[3])
        : "r"(a0), "r"(0u), "r"(a2), "r"(0u), "r"(b0), "r"(b1));
}
__device__ __forceinline__ uint4 ld_relaxed_v4(const void* p) {
    uint4 v;
    asm volatile("ld.relaxed.gpu.global.v4.u32 {%0,%1,%2,%3}, [%4];" : "=r"(v.x), "=r"(v.y), "=r"(v.z), "=r"(v.w) : "l"(p) : "memory");
    return v;
}
__device__ __forceinline__ uint2 ld_relaxed_v2(const void* p) {
    uint2 v;
    asm volatile("ld.relaxed.gpu.global.v2.u32 {%0,%1}, [%2];" : "=r"(v.x), "=r"(v.y) : "l"(p) : "memory");
    return v;
}
__device__ __forceinline__ void st_relaxed_v4(void* p, uint4 v) {
    asm volatile("st.relaxed.gpu.global.v4.u32 [%0], {%1,%2,%3,%4};" ::"l"(p), "r"(v.x), "r"(v.y), "r"(v.z), "r"(v.w) : "memory");
}
__device__ __forceinline__ void st_relaxed_v2(void* p, uint2 v) {
    asm volatile("st.relaxed.gpu.global.v2.u32 [%0], {%1,%2};" ::"l"(p), "r"(v.x), "r"(v.y) : "memory");
}
__device__ __forceinline__ void st_relaxed_u32(void* p, uint32_t v) {
    asm volatile("st.relaxed.gpu.global.u32 [%0], %1;" ::"l"(p), "r"(v) : "memory");
}
__device__ __forceinline__ uint4 ld_nc_v4(const void* p) {
    uint4 v;
    asm volatile("ld.global.nc.L1::no_allocate.L2::256B.v4.u32 {%0,%1,%2,%3}, [%4];" : "=r"(v.x), "=r"(v.y), "=r"(v.z), "=r"(v.w) : "l"(p));
    return v;
}
__device__ __forceinline__ uint32_t ld_nc_u16(const void* p) {
    unsigned short v;
    asm volatile("ld.global.nc.u16 %0, [%1];" : "=h"(v) : "l"(p));
    return (uint32_t)v;
}
__device__ __forceinline__ uint32_t enc(float f) {
    uint32_t u = __float_as_uint(f);
    return u == 0u ? 0x80000000u : u;
}
__device__ __forceinline__ bool valid4(const uint4& v) { return v.x != 0u && v.y != 0u && v.z != 0u && v.w != 0u; }
__device__ __forceinline__ float bf_lo(uint32_t w) { return __uint_as_float(w << 16); }
__device__ __forceinline__ float bf_hi(uint32_t w) { return __uint_as_float(w & 0xffff0000u); }
__device__ __forceinline__ uint32_t pack_bf16(float lo, float hi) {
    uint32_t r;
    asm("cvt.rn.bf16x2.f32 %0, %1, %2;" : "=r"(r) : "f"(hi), "f"(lo));
    return r;
}
__device__ __forceinline__ float ex2(float x) {
    float y;
    asm("ex2.approx.ftz.f32 %0, %1;" : "=f"(y) : "f"(x));
    return y;
}

constexpr float kScale = 0.08838834764831845f;
constexpr float kLog2e = 1.4426950408889634f;
__device__ __forceinline__ float2 round_scores(float a, float b) {
    const uint32_t r1 = pack_bf16(a, b);
    const uint32_t r2 = pack_bf16(bf_lo(r1) * kScale, bf_hi(r1) * kScale);
    return make_float2(bf_lo(r2), bf_hi(r2));
}

__device__ __forceinline__ void red_add(unsigned int* p, unsigned int v) {
    asm volatile("red.relaxed.gpu.global.add.u32 [%0], %1;" ::"l"(p), "r"(v) : "memory");
}
__device__ __forceinline__ uint32_t ld_relaxed_u32(const void* p) {
    uint32_t v;
    asm volatile("ld.relaxed.gpu.global.u32 %0, [%1];" : "=r"(v) : "l"(p) : "memory");
    return v;
}
__device__ __forceinline__ void wait_count(const unsigned int* p, unsigned int target, unsigned ns) {
    uint32_t n = 0;
    while (ld_relaxed_u32(p) < target) {
        __nanosleep(ns);
        if (++n > SPIN_LIMIT) __trap();
    }
}
__device__ __forceinline__ void wait_front(const volatile int* front, int target) {
    uint32_t n = 0;
    while (*front < target) {
        __nanosleep(100);
        if (++n > SPIN_LIMIT) __trap();
    }
}

__global__ void __launch_bounds__(NTHREADS, 1)
gqa_fused_kernel(const __nv_bfloat16* __restrict__ x, const __nv_bfloat16* __restrict__ wq,
                 const __nv_bfloat16* __restrict__ wo, __nv_bfloat16* __restrict__ out,
                 const __grid_constant__ CUtensorMap tmK, const __grid_constant__ CUtensorMap tmV) {
    extern __shared__ uint8_t smem_raw[];
    const uint32_t raw_u32 = smem_u32(smem_raw);
    const uint32_t sb = (raw_u32 + 1023u) & ~1023u;
    uint8_t* sm = smem_raw + (sb - raw_u32);

    const int tid = threadIdx.x, warp = tid >> 5, lane = tid & 31;
    const int cta = blockIdx.x;
    const uint32_t bar_full = sb + SM_BAR, bar_empty = bar_full + 8 * STAGES, bar_wo = bar_empty + 8 * STAGES;
    volatile int* tidx = reinterpret_cast<volatile int*>(sm + SM_TIDX);
    volatile int* front = reinterpret_cast<volatile int*>(sm + SM_FRONT);
    volatile int* qflag = reinterpret_cast<volatile int*>(sm + SM_QFLAG);

    if (warp == 8) {
        uint64_t pol = 0;
        int s = 0, it = 0, t = cta;
        uint32_t ph = 1;
        unsigned nxt = 0;
        bool done = false;
        auto issue = [&]() {
            if (it >= STAGES) mbar_wait(bar_empty + 8 * s, ph);
            const uint32_t fb = bar_full + 8 * s;
            if (t >= NTILES) {
                STAMP(3);
                tidx[s] = -1;
                *front = NTILES;
                mbar_arrive(fb);
                done = true;
                return;
            }
            tidx[s] = t;
            *front = t;
            mbar_expect_tx(fb, STAGE_BYTES);
            const uint32_t dk = sb + SM_RING + s * STAGE_BYTES, dv = dk + TILE_BYTES;
            const int row = t * TILE;
            tma2d(dk, &tmK, 0, row, fb, pol);
            tma2d(dk + HALF_BYTES, &tmK, 64, row, fb, pol);
            tma2d(dv, &tmV, 0, row, fb, pol);
            tma2d(dv + HALF_BYTES, &tmV, 64, row, fb, pol);
            ++it;
            if (it < STAGES) {
                t = it * NCTA + cta;
            } else {
                t = STAGES * NCTA + (int)nxt;
                if (t < NTILES) nxt = atomicAdd(&g_ctr, 1u);
            }
            if (++s == STAGES) { s = 0; ph ^= 1; }
        };
        qflag[lane] = 0;
        if (lane == 0) {
            STAMP(0);
            asm volatile("prefetch.tensormap [%0];" ::"l"(&tmK) : "memory");
            asm volatile("prefetch.tensormap [%0];" ::"l"(&tmV) : "memory");
            for (int i = 0; i < STAGES; i++) {
                mbar_init(bar_full + 8 * i, 1);
                mbar_init(bar_empty + 8 * i, 4);
            }
            mbar_init(bar_wo, 1);
            asm volatile("fence.mbarrier_init.release.cluster;" ::: "memory");
            asm volatile("createpolicy.fractional.L2::evict_first.b64 %0, 1.0;" : "=l"(pol));
            for (int i = 0; i < EARLY_STAGES; i++) issue();
            nxt = atomicAdd(&g_ctr, 1u);
        }
        __syncwarp();
        named_bar(0, NTHREADS);
        if (cta < NJOB) named_bar(1, NTHREADS);
        if (lane == 0) {
            while (!done) issue();
        }
        return;
    }

    uint4 wv[9];
    uint32_t xa[9], xb[9];
    if (cta < NJOB) {
        const int rg = tid >> 2, ch = tid & 3;
#pragma unroll
        for (int i = 0; i < 9; i++)
            wv[i] = ld_nc_v4(wq + (size_t)(rg + 64 * i) * (kHQ * kDH) + cta * 32 + ch * 8);
#pragma unroll
        for (int i = 0; i < 9; i++) {
            xa[i] = ld_nc_u16(x + rg + 64 * i);
            xb[i] = ld_nc_u16(x + kD + rg + 64 * i);
        }
    }
    named_bar(0, NTHREADS);

    {
        float* red = reinterpret_cast<float*>(sm + SM_RED);
        if (cta < NJOB) {
            float acc[2][8];
#pragma unroll
            for (int c = 0; c < 8; c++) acc[0][c] = acc[1][c] = 0.f;
#pragma unroll
            for (int i = 0; i < 9; i++) {
                const float fa = __uint_as_float(xa[i] << 16), fb = __uint_as_float(xb[i] << 16);
                const uint32_t w4[4] = {wv[i].x, wv[i].y, wv[i].z, wv[i].w};
#pragma unroll
                for (int c = 0; c < 4; c++) {
                    const float lo = bf_lo(w4[c]), hi = bf_hi(w4[c]);
                    acc[0][2 * c] = fmaf(fa, lo, acc[0][2 * c]);
                    acc[0][2 * c + 1] = fmaf(fa, hi, acc[0][2 * c + 1]);
                    acc[1][2 * c] = fmaf(fb, lo, acc[1][2 * c]);
                    acc[1][2 * c + 1] = fmaf(fb, hi, acc[1][2 * c + 1]);
                }
            }
#pragma unroll
            for (int b = 0; b < 2; b++)
#pragma unroll
                for (int c = 0; c < 8; c++) {
                    float v = acc[b][c];
                    v += __shfl_xor_sync(0xffffffffu, v, 4);
                    v += __shfl_xor_sync(0xffffffffu, v, 8);
                    v += __shfl_xor_sync(0xffffffffu, v, 16);
                    acc[b][c] = v;
                }
            if (lane < 4) {
#pragma unroll
                for (int b = 0; b < 2; b++)
#pragma unroll
                    for (int c = 0; c < 8; c++) red[warp * 64 + b * 32 + lane * 8 + c] = acc[b][c];
            }
            named_bar(1, NTHREADS);
            if (tid == 0) STAMP(1);
            if (tid < 32) {
                float s0 = 0.f, s1 = 0.f;
#pragma unroll
                for (int w = 0; w < 8; w++) {
                    s0 += red[w * 64 + 2 * tid];
                    s1 += red[w * 64 + 2 * tid + 1];
                }
                uint32_t word = pack_bf16(s0, s1);
                if (word == 0u) word = 0x80008000u;
                st_relaxed_u32(&g_q[(tid >> 4) * 2048 + cta * 16 + (tid & 15)], word);
            }
        }
    }

    if (warp < 4) {
        const int g8 = lane >> 2, j = lane & 3, head = g8 & 1;
        const int l7 = lane & 7, mi = lane >> 3;
        uint32_t qf[8][2];
        float o[4][4];
        float m_run = -INFINITY, l_run = 0.f;
#pragma unroll
        for (int n = 0; n < 4; n++) o[n][0] = o[n][1] = o[n][2] = o[n][3] = 0.f;
#pragma unroll
        for (int k = 0; k < 8; k++) qf[k][0] = qf[k][1] = 0u;
        int cur_g = -1;
        int s = 0;
        uint32_t ph = 0, par = 0;
        const uint32_t koff = (uint32_t)((warp * KPW + l7) * 128);
        const uint32_t kc0 = (uint32_t)(((mi) ^ l7) << 4), kc1 = (uint32_t)(((4 + mi) ^ l7) << 4);
        const uint32_t voff = (uint32_t)(TILE_BYTES + (warp >> 1) * HALF_BYTES + ((mi & 1) * 8 + l7) * 128);
        const uint32_t vc0 = (uint32_t)((((warp & 1) * 4 + (mi >> 1)) ^ l7) << 4);
        const uint32_t vc1 = (uint32_t)((((warp & 1) * 4 + 2 + (mi >> 1)) ^ l7) << 4);

        while (true) {
            mbar_wait(bar_full + 8 * s, ph);
            const int t = tidx[s];
            const int g = t < 0 ? kNG : t / TPG;
            if (g != cur_g) {
                if (t < 0 && tid == 0) STAMP(21);
                float lt = l_run;
                lt += __shfl_xor_sync(0xffffffffu, lt, 1);
                lt += __shfl_xor_sync(0xffffffffu, lt, 2);
                for (int gg = (cur_g < 0 ? 0 : cur_g); gg < g; gg++) {
                    const bool real = (gg == cur_g);
                    if (!real) {
                        uint32_t n = 0;
                        while (qflag[gg] == 0) {
                            if (++n > SPIN_LIMIT) __trap();
                        }
                    }
                    const int e = head * 4 + warp;
                    const int nsel = g8 >> 1;
                    float v0 = nsel == 0 ? o[0][0] : nsel == 1 ? o[1][0] : nsel == 2 ? o[2][0] : o[3][0];
                    float v1 = nsel == 0 ? o[0][1] : nsel == 1 ? o[1][1] : nsel == 2 ? o[2][1] : o[3][1];
                    if (!real) v0 = v1 = 0.f;
                    st_relaxed_v2(&g_po[gg][e][cta][nsel * 8 + 2 * j], make_uint2(enc(v0), enc(v1)));
                    if (lane < 8 && j == 0)
                        st_relaxed_v2(&g_pml[gg][e][cta], make_uint2(enc(real ? m_run : -INFINITY), enc(real ? lt : 0.f)));
                    if (lane == 0 && gg != kNG - 1) red_add(&g_done[gg * 32], 1u);
                }
                if (t < 0) { if (tid == 0) STAMP(4); break; }
                cur_g = g;
                m_run = -INFINITY;
                l_run = 0.f;
#pragma unroll
                for (int n = 0; n < 4; n++) o[n][0] = o[n][1] = 0.f;
                {
                    uint32_t n = 0;
                    while (qflag[g] == 0) {
                        if (++n > SPIN_LIMIT) __trap();
                    }
                    __threadfence_block();
                    if (tid == 0 && g == 0) STAMP(2);
                }
                const volatile uint32_t* qs = reinterpret_cast<const volatile uint32_t*>(sm + SM_Q) + g * 128 + head * 64 + j;
#pragma unroll
                for (int k = 0; k < 8; k++) {
                    qf[k][0] = qs[k * 8];
                    qf[k][1] = qs[k * 8 + 4];
                }
            }
            const uint32_t st = sb + SM_RING + s * STAGE_BYTES;
            float sc[NT_QK][2][4];
#pragma unroll
            for (int nt = 0; nt < NT_QK; nt++) {
#pragma unroll
                for (int h = 0; h < 2; h++) sc[nt][h][0] = sc[nt][h][1] = sc[nt][h][2] = sc[nt][h][3] = 0.f;
#pragma unroll
                for (int h = 0; h < 2; h++) {
                    uint32_t r0, r1, r2, r3;
                    ldsm4(st + koff + nt * 1024 + h * HALF_BYTES + kc0, r0, r1, r2, r3);
                    mma_bf16(sc[nt][h], qf[4 * h][0], qf[4 * h][1], r0, r1);
                    mma_bf16(sc[nt][h], qf[4 * h + 1][0], qf[4 * h + 1][1], r2, r3);
                    ldsm4(st + koff + nt * 1024 + h * HALF_BYTES + kc1, r0, r1, r2, r3);
                    mma_bf16(sc[nt][h], qf[4 * h + 2][0], qf[4 * h + 2][1], r0, r1);
                    mma_bf16(sc[nt][h], qf[4 * h + 3][0], qf[4 * h + 3][1], r2, r3);
                }
            }
            float2* sx = reinterpret_cast<float2*>(sm + SM_SX) + par * (TILE / 8) * 8;
            if (lane < 8) {
#pragma unroll
                for (int nt = 0; nt < NT_QK; nt++)
                    sx[(warp * NT_QK + nt) * 8 + lane] =
                        round_scores(sc[nt][0][0] + sc[nt][1][0], sc[nt][0][1] + sc[nt][1][1]);
            }
            named_bar(2, 128);
            float2 sv[TILE / 8];
#pragma unroll
            for (int n = 0; n < TILE / 8; n++) sv[n] = sx[n * 8 + head * 4 + j];
            float mx = fmaxf(sv[0].x, sv[0].y);
#pragma unroll
            for (int n = 1; n < TILE / 8; n++) mx = fmaxf(mx, fmaxf(sv[n].x, sv[n].y));
            mx = fmaxf(mx, __shfl_xor_sync(0xffffffffu, mx, 1));
            mx = fmaxf(mx, __shfl_xor_sync(0xffffffffu, mx, 2));
            const float m_new = fmaxf(m_run, mx);
            const float alpha = ex2((m_run - m_new) * kLog2e);
            const float mb = m_new * kLog2e;
            m_run = m_new;
            uint32_t pf[TILE / 8];
            float ls = 0.f;
#pragma unroll
            for (int n = 0; n < TILE / 8; n++) {
                const float p0 = ex2(fmaf(sv[n].x, kLog2e, -mb));
                const float p1 = ex2(fmaf(sv[n].y, kLog2e, -mb));
                ls += p0 + p1;
                pf[n] = pack_bf16(p0, p1);
            }
            l_run = fmaf(l_run, alpha, ls);
#pragma unroll
            for (int n = 0; n < 4; n++) {
                o[n][0] *= alpha;
                o[n][1] *= alpha;
            }
#pragma unroll
            for (int kb = 0; kb < NKB; kb++) {
                uint32_t r0, r1, r2, r3;
                ldsm4t(st + voff + kb * 2048 + vc0, r0, r1, r2, r3);
                mma_bf16(o[0], pf[2 * kb], pf[2 * kb + 1], r0, r1);
                mma_bf16(o[1], pf[2 * kb], pf[2 * kb + 1], r2, r3);
                ldsm4t(st + voff + kb * 2048 + vc1, r0, r1, r2, r3);
                mma_bf16(o[2], pf[2 * kb], pf[2 * kb + 1], r0, r1);
                mma_bf16(o[3], pf[2 * kb], pf[2 * kb + 1], r2, r3);
            }
            __syncwarp();
            if (lane == 0) mbar_arrive(bar_empty + 8 * s);
            par ^= 1;
            if (++s == STAGES) { s = 0; ph ^= 1; }
        }
        return;
    }

    const int et = tid - 128, ew = warp - 4;
    for (int g = ew; g < kNG; g += 4) {
        uint4 qv;
        uint32_t n = 0;
        while (true) {
            qv = ld_relaxed_v4(&g_q[g * 128 + lane * 4]);
            if (__all_sync(0xffffffffu, valid4(qv))) break;
            if (++n > SPIN_LIMIT) __trap();
        }
        *reinterpret_cast<uint4*>(sm + SM_Q + g * 512 + lane * 16) = qv;
        __threadfence_block();
        __syncwarp();
        if (lane == 0) qflag[g] = 1;
    }
    if (cta < NJOB) {
        const int hkv = cta >> 3, e = cta & 7;
        if (ew == 0) {
            if (lane == 0) mbar_expect_tx(bar_wo, 32 * WO_ROW);
            __syncwarp();
            bulk_load(sb + SM_WO + lane * WO_PITCH, wo + (size_t)(cta * 32 + lane) * kD, WO_ROW, bar_wo);
        }
        float* red = reinterpret_cast<float*>(sm + SM_RED);
        const int ch = et & 7, c0 = et >> 3, g8 = lane >> 2, j = lane & 3;
        for (int b = 0; b < kB; b++) {
            const int g = b * kHKV + hkv;
            wait_front(front, (g + 1) * TPG);
            if (et == 0) STAMP(7 + 3 * b);
            if (g != kNG - 1) {
                if (et == 0) wait_count(&g_done[g * 32], 4 * NCTA, 200);
                named_bar(3, 128);
            }
            uint4 ov[9];
            uint2 mv[5];
#pragma unroll
            for (int i = 0; i < 9; i++) {
                const bool use = (c0 + 16 * i) < NCTA;
                ov[i] = use ? make_uint4(0, 0, 0, 0) : make_uint4(0x80000000u, 0x80000000u, 0x80000000u, 0x80000000u);
            }
#pragma unroll
            for (int i = 0; i < 5; i++) {
                const bool use = (lane + 32 * i) < NCTA;
                mv[i] = use ? make_uint2(0, 0) : make_uint2(0xff800000u, 0x80000000u);
            }
            uint32_t n = 0;
            while (true) {
                bool ok = true;
#pragma unroll
                for (int i = 0; i < 5; i++)
                    if (mv[i].x == 0u || mv[i].y == 0u) mv[i] = ld_relaxed_v2(&g_pml[g][e][lane + 32 * i]);
#pragma unroll
                for (int i = 0; i < 9; i++)
                    if (!valid4(ov[i])) ov[i] = ld_relaxed_v4(&g_po[g][e][c0 + 16 * i][ch * 4]);
#pragma unroll
                for (int i = 0; i < 5; i++) ok = ok && mv[i].x != 0u && mv[i].y != 0u;
#pragma unroll
                for (int i = 0; i < 9; i++) ok = ok && valid4(ov[i]);
                if (__all_sync(0xffffffffu, ok)) break;
                if (++n > SPIN_LIMIT) __trap();
            }
            if (et == 0) STAMP(5 + 3 * b);
            if (lane == 0 && b == 1) STAMP(16 + ew);
            float M = -INFINITY;
#pragma unroll
            for (int i = 0; i < 5; i++) M = fmaxf(M, __uint_as_float(mv[i].x));
#pragma unroll
            for (int d = 16; d > 0; d >>= 1) M = fmaxf(M, __shfl_xor_sync(0xffffffffu, M, d));
            float wc[5], L = 0.f;
#pragma unroll
            for (int i = 0; i < 5; i++) {
                wc[i] = ex2((__uint_as_float(mv[i].x) - M) * kLog2e);
                L = fmaf(wc[i], __uint_as_float(mv[i].y), L);
            }
#pragma unroll
            for (int d = 16; d > 0; d >>= 1) L += __shfl_xor_sync(0xffffffffu, L, d);
            float a0 = 0.f, a1 = 0.f, a2 = 0.f, a3 = 0.f;
#pragma unroll
            for (int i = 0; i < 9; i++) {
                const float w = __shfl_sync(0xffffffffu, wc[i >> 1], c0 + 16 * (i & 1));
                a0 = fmaf(w, __uint_as_float(ov[i].x), a0);
                a1 = fmaf(w, __uint_as_float(ov[i].y), a1);
                a2 = fmaf(w, __uint_as_float(ov[i].z), a2);
                a3 = fmaf(w, __uint_as_float(ov[i].w), a3);
            }
#pragma unroll
            for (int d = 8; d <= 16; d <<= 1) {
                a0 += __shfl_xor_sync(0xffffffffu, a0, d);
                a1 += __shfl_xor_sync(0xffffffffu, a1, d);
                a2 += __shfl_xor_sync(0xffffffffu, a2, d);
                a3 += __shfl_xor_sync(0xffffffffu, a3, d);
            }
            if (lane < 8) *reinterpret_cast<float4*>(red + ew * 32 + lane * 4) = make_float4(a0, a1, a2, a3);
            if (b == 0) mbar_wait(bar_wo, 0);
            named_bar(3, 128);
            if (et == 0 && b == 1) STAMP(20);
            const float rl = 1.0f / L;
            uint32_t af[4];
#pragma unroll
            for (int k = 0; k < 4; k++) {
                float2 v = *reinterpret_cast<const float2*>(red + k * 8 + 2 * j);
#pragma unroll
                for (int w = 1; w < 4; w++) {
                    const float2 u = *reinterpret_cast<const float2*>(red + w * 32 + k * 8 + 2 * j);
                    v.x += u.x;
                    v.y += u.y;
                }
                af[k] = pack_bf16(v.x * rl, v.y * rl);
            }
            {
                const uint32_t wbase = sb + SM_WO + lane * WO_PITCH + ew * 288;
                float* dst = &g_op[b][hkv][e][ew * 144 + g8 * 8 + 2 * j];
#pragma unroll
                for (int bt = 0; bt < 3; bt++) {
                    float r0 = 0.f, r1 = 0.f;
#pragma unroll
                    for (int tt = 0; tt < (bt < 2 ? 8 : 2); tt++) {
                        uint32_t b0, b1, b2, b3;
                        ldsm4t(wbase + (bt * 8 + tt) * 16, b0, b1, b2, b3);
                        float c[4] = {0.f, 0.f, 0.f, 0.f};
                        mma_bf16(c, af[0], af[1], b0, b1);
                        mma_bf16(c, af[2], af[3], b2, b3);
                        if (g8 == tt) { r0 = c[0]; r1 = c[1]; }
                    }
                    if (bt < 2 || g8 < 2) st_relaxed_v2(dst + bt * 64, make_uint2(enc(r0), enc(r1)));
                }
            }
            if (lane == 0 && g != kNG - 1) red_add(&g_done2[g * 32 + (ew >> 1) * 16], 1u);
            if (et == 0) STAMP(6 + 3 * b);
#pragma unroll
            for (int i = 0; i < 9; i++)
                if ((c0 + 16 * i) < NCTA) st_relaxed_v4(&g_po[g][e][c0 + 16 * i][ch * 4], make_uint4(0, 0, 0, 0));
            st_relaxed_v2(&g_pml[g][e][et], make_uint2(0, 0));
            if (et < NCTA - 128) st_relaxed_v2(&g_pml[g][e][128 + et], make_uint2(0, 0));
            named_bar(3, 128);
        }
        if (et < 32) st_relaxed_u32(&g_q[(et >> 4) * 2048 + cta * 16 + (et & 15)], 0u);
    } else {
        const int b = (cta - NJOB) >> 1, half = (cta - NJOB) & 1;
        if (ew < 3) {
            float a0 = 0.f, a1 = 0.f, a2 = 0.f, a3 = 0.f;
            const int col = half * 288 + et * 4;
            for (int hkv = 0; hkv < kHKV; hkv++) {
                const int g = b * kHKV + hkv;
                wait_front(front, (g + 1) * TPG);
                if (g != kNG - 1) {
                    if (et == 0) wait_count(&g_done2[g * 32 + half * 16], 16, 200);
                    named_bar(3, 96);
                }
                if (et < 72) {
                    uint4 pv[8];
#pragma unroll
                    for (int i = 0; i < 8; i++) pv[i] = make_uint4(0, 0, 0, 0);
                    uint32_t n = 0;
                    while (true) {
                        bool ok = true;
#pragma unroll
                        for (int i = 0; i < 8; i++)
                            if (!valid4(pv[i])) pv[i] = ld_relaxed_v4(&g_op[b][hkv][i][col]);
#pragma unroll
                        for (int i = 0; i < 8; i++) ok = ok && valid4(pv[i]);
                        if (ok) break;
                                if (++n > SPIN_LIMIT) __trap();
                    }
                    if (hkv == kHKV - 1 && lane == 0) STAMP(22 + ew);
#pragma unroll
                    for (int i = 0; i < 8; i++) {
                        a0 += __uint_as_float(pv[i].x);
                        a1 += __uint_as_float(pv[i].y);
                        a2 += __uint_as_float(pv[i].z);
                        a3 += __uint_as_float(pv[i].w);
                    }
                    if (hkv == kHKV - 1) {
                        uint2 r = make_uint2(pack_bf16(a0, a1), pack_bf16(a2, a3));
                        *reinterpret_cast<uint2*>(out + b * kD + col) = r;
                        if (et == 0) STAMP(11);
                        if (cta == NCTA - 1 && et == 0) st_relaxed_u32(&g_ctr, 0u);
                        if (et < kHKV) {
                            if (half == 0) st_relaxed_u32(&g_done[(b * kHKV + et) * 32], 0u);
                            st_relaxed_u32(&g_done2[(b * kHKV + et) * 32 + half * 16], 0u);
                        }
                    }
#pragma unroll
                    for (int i = 0; i < 8; i++) st_relaxed_v4(&g_op[b][hkv][i][col], make_uint4(0, 0, 0, 0));
                }
            }
        }
    }
}

__global__ void fb_qproj(const __nv_bfloat16* x, const __nv_bfloat16* wq) {
    const int idx = blockIdx.x * blockDim.x + threadIdx.x;
    const int b = idx / (kHQ * kDH), c = idx % (kHQ * kDH);
    float a = 0.f;
    for (int k = 0; k < kD; k++) a = fmaf(__bfloat162float(x[b * kD + k]), __bfloat162float(wq[(size_t)k * kHQ * kDH + c]), a);
    f_q[idx] = __bfloat162float(__float2bfloat16_rn(a));
}
__global__ void fb_attn(const __nv_bfloat16* K, const __nv_bfloat16* V) {
    __shared__ float sp[512];
    __shared__ float sred[128];
    const int split = blockIdx.x, bh = blockIdx.y, tid = threadIdx.x;
    const int b = bh / kHQ, h = bh % kHQ;
    const size_t base = ((size_t)(b * kHKV + h / 2) * kSK + split * 512) * kDH;
    const float* q = f_q + bh * kDH;
    float mx = -INFINITY;
    for (int k = tid; k < 512; k += 128) {
        float a = 0.f;
        for (int d = 0; d < kDH; d++) a = fmaf(q[d], __bfloat162float(K[base + (size_t)k * kDH + d]), a);
        a = round_scores(a, 0.f).x;
        sp[k] = a;
        mx = fmaxf(mx, a);
    }
    sred[tid] = mx;
    __syncthreads();
    for (int s = 64; s > 0; s >>= 1) { if (tid < s) sred[tid] = fmaxf(sred[tid], sred[tid + s]); __syncthreads(); }
    mx = sred[0];
    __syncthreads();
    float l = 0.f;
    for (int k = tid; k < 512; k += 128) { float p = exp2f((sp[k] - mx) * kLog2e); sp[k] = p; l += p; }
    sred[tid] = l;
    __syncthreads();
    for (int s = 64; s > 0; s >>= 1) { if (tid < s) sred[tid] += sred[tid + s]; __syncthreads(); }
    float a = 0.f;
    for (int k = 0; k < 512; k++) a = fmaf(sp[k], __bfloat162float(V[base + (size_t)k * kDH + tid]), a);
    f_po[bh][split][tid] = a;
    if (tid == 0) f_pml[bh][split] = make_float2(mx, sred[0]);
}
__global__ void fb_combine() {
    const int bh = blockIdx.x, tid = threadIdx.x;
    float M = -INFINITY;
    for (int s = 0; s < 64; s++) M = fmaxf(M, f_pml[bh][s].x);
    float L = 0.f, a = 0.f;
    for (int s = 0; s < 64; s++) {
        const float w = exp2f((f_pml[bh][s].x - M) * kLog2e);
        L = fmaf(w, f_pml[bh][s].y, L);
        a = fmaf(w, f_po[bh][s][tid], a);
    }
    f_o[bh * kDH + tid] = __bfloat162float(__float2bfloat16_rn(a / L));
}
__global__ void fb_oproj(const __nv_bfloat16* wo, __nv_bfloat16* out) {
    const int idx = blockIdx.x * blockDim.x + threadIdx.x;
    if (idx >= kB * kD) return;
    const int b = idx / kD, c = idx % kD;
    float a = 0.f;
    for (int k = 0; k < kHQ * kDH; k++) a = fmaf(f_o[b * kHQ * kDH + k], __bfloat162float(wo[(size_t)k * kD + c]), a);
    out[idx] = __float2bfloat16_rn(a);
}

typedef CUresult (*EncodeFn)(CUtensorMap*, CUtensorMapDataType, cuuint32_t, void*, const cuuint64_t*, const cuuint64_t*,
                             const cuuint32_t*, const cuuint32_t*, CUtensorMapInterleave, CUtensorMapSwizzle,
                             CUtensorMapL2promotion, CUtensorMapFloatOOBfill);

bool make_map(EncodeFn enc_fn, CUtensorMap* tm, const void* p) {
    cuuint64_t gd[2] = {(cuuint64_t)kDH, (cuuint64_t)kNG * kSK};
    cuuint64_t gs[1] = {(cuuint64_t)kDH * 2};
    cuuint32_t bx[2] = {64, (cuuint32_t)TILE};
    cuuint32_t es[2] = {1, 1};
    return enc_fn(tm, CU_TENSOR_MAP_DATA_TYPE_BFLOAT16, 2, const_cast<void*>(p), gd, gs, bx, es,
                  CU_TENSOR_MAP_INTERLEAVE_NONE, CU_TENSOR_MAP_SWIZZLE_128B, CU_TENSOR_MAP_L2_PROMOTION_L2_256B,
                  CU_TENSOR_MAP_FLOAT_OOB_FILL_NONE) == CUDA_SUCCESS;
}

}

extern "C" void kernel_launch(void* const* d_in, const int* in_sizes, int n_in, void* d_out, int out_size) {
    const __nv_bfloat16* x = (const __nv_bfloat16*)d_in[0];
    const __nv_bfloat16* K = (const __nv_bfloat16*)d_in[1];
    const __nv_bfloat16* V = (const __nv_bfloat16*)d_in[2];
    const __nv_bfloat16* wq = (const __nv_bfloat16*)d_in[3];
    const __nv_bfloat16* wo = (const __nv_bfloat16*)d_in[4];
    __nv_bfloat16* out = (__nv_bfloat16*)d_out;

    static int mode = -1;
    static EncodeFn enc_fn = nullptr;
    if (mode < 0) {
        mode = 0;
        int dev = 0, sms = 0, occ = 0;
        cudaGetDevice(&dev);
        cudaDeviceGetAttribute(&sms, cudaDevAttrMultiProcessorCount, dev);
        cudaDriverEntryPointQueryResult qr;
        void* fn = nullptr;
        if (cudaGetDriverEntryPoint("cuTensorMapEncodeTiled", &fn, cudaEnableDefault, &qr) == cudaSuccess && fn &&
            cudaFuncSetAttribute(gqa_fused_kernel, cudaFuncAttributeMaxDynamicSharedMemorySize, SMEM_BYTES) == cudaSuccess &&
            cudaOccupancyMaxActiveBlocksPerMultiprocessor(&occ, gqa_fused_kernel, NTHREADS, SMEM_BYTES) == cudaSuccess &&
            occ >= 1 && sms >= NCTA) {
            enc_fn = (EncodeFn)fn;
            mode = 1;
        }
        (void)cudaGetLastError();
    }
    if (mode == 1) {
        CUtensorMap tmK, tmV;
        if (make_map(enc_fn, &tmK, K) && make_map(enc_fn, &tmV, V)) {
            gqa_fused_kernel<<<NCTA, NTHREADS, SMEM_BYTES>>>(x, wq, wo, out, tmK, tmV);
            return;
        }
    }
    fb_qproj<<<32, 256>>>(x, wq);
    fb_attn<<<dim3(64, 64), 128>>>(K, V);
    fb_combine<<<64, 128>>>();
    fb_oproj<<<9, 128>>>(wo, out);
}
```
